```python
import torch

def _softmax(x, axis=-1):
    return torch.softmax(x, dim=axis)
def _gelu(x):
    return torch.nn.functional.gelu(x, approximate="tanh")
def _silu(x):
    return torch.nn.functional.silu(x)
def _sigmoid(x):
    return torch.sigmoid(x)
def _layernorm(x, axis=-1, eps=1e-5):
    m = x.mean(dim=axis, keepdim=True)
    v = x.var(dim=axis, keepdim=True, unbiased=False)
    return (x - m) / torch.sqrt(v + eps)
def _scatter_add(tgt, idx, src, axis=0):
    return tgt.clone().index_add_(axis, idx, src)
def _segment_sum(src, seg, n):
    out = torch.zeros((n,) + src.shape[1:], dtype=src.dtype)
    return out.index_add_(0, seg, src)
def _pad(x, pw):
    flat = tuple(v for pair in reversed(pw) for v in pair)
    return torch.nn.functional.pad(x, flat)

kernel_name = 'standalone__depthwise_separable__vision'

def setup_inputs():

    _w = (lambda a: (lambda t: t.to(torch.bfloat16) if t.is_floating_point() else t)(torch.as_tensor(a)))
    H = W = 384
    C = 384
    k = 1
    return {
        "x": _w((lambda *s: torch.randn(*s, dtype=torch.bfloat16) * 0.05)(1, H, W, C)),
        "dw": _w((lambda *s: torch.randn(*s, dtype=torch.bfloat16) * 0.05)(k, k, C)),
        "pw": _w((lambda *s: torch.randn(*s, dtype=torch.bfloat16) * 0.05)(C, C)),
    }

def reference(x, dw, pw):
    B, H, W, C = x.shape
    k = dw.shape[0]
    pad = k // 2
    xp = _pad(x, ((0,0),(pad,pad),(pad,pad),(0,0)))
    out = torch.zeros_like(x)
    for i in range(k):
        for j in range(k):
            out = out + xp[:, i:i+H, j:j+W, :] * dw[i, j][None, None, None, :]
    return torch.einsum('bhwc,cd->bhwd', out, pw)
```

```cpp
#include <cuda_runtime.h>
#include <cuda_bf16.h>
#include <cuda.h>
#include <stdint.h>

namespace {

constexpr int kC = 384;
constexpr int kTilePx = 32;
constexpr int kStages = 5;
constexpr int kOutBufs = 8;
constexpr int kPark = 5;
constexpr int kThreads = 512;
constexpr int kStageBytes = kTilePx * kC * 2;
constexpr int kOutBytes = kTilePx * 192 * 2;
constexpr int kWChunkBytes = 64 * 192 * 2;
constexpr int kXSlabBytes = 64 * 128 * 2;
constexpr int kWOff = 2 * kStageBytes;
constexpr int kOutOff = kStages * kStageBytes;
constexpr int kSpillOff = kOutOff + kOutBufs * kOutBytes;
constexpr int kDwOff = kSpillOff;
constexpr int kFullOff = kSpillOff + 384 * 28;
constexpr int kEmptyOff = kFullOff + 8 * kStages;
constexpr int kOFullOff = kEmptyOff + 8 * kStages;
constexpr int kOEmptyOff = kOFullOff + 8 * kOutBufs;
constexpr int kWBarOff = kOEmptyOff + 8 * kOutBufs;
constexpr int kXBarOff = kWBarOff + 8 * 3;
constexpr int kDwBarOff = kXBarOff + 8 * 3;
constexpr int kSlotOff = kDwBarOff + 8;
constexpr int kOSlotOff = kSlotOff + 4 * kStages;
constexpr int kPSlotOff = kOSlotOff + 4 * kOutBufs;
constexpr int kScratchOff = kPSlotOff + 4 * (kPark + 1);
constexpr int kSmemBytes = kScratchOff + 128;
static_assert(kWChunkBytes == kStageBytes && kWOff + 6 * kWChunkBytes <= kDwOff, "weight staging");
static_assert(kSmemBytes <= 232448, "shared memory");

struct Knobs {
    int first_gap;
    int pf_t0, pf_dt;
    int pull_to;
    int static_tiles;
    int mid_from, mid_to, mid_n;
    int park_from;
    int stream_from;
    int lag;
    int hold_pos[6], hold[6];
    int lead_pos[8], lead[8];
    int lead_slope[8];
};
#define DEFAULT_KNOBS {514, 280, 840, 528, 18, 1810, 2600, 2, 3430, 4420, 2, \
    {0, 440, 721, 1081, 4260, 4608}, {0, 1, 2, 3, 1, 1}, \
    {845, 1485, 1890, 2220, 2245, 3442, 4120, 4500}, {380, 543, 350, 314, 350, 84, 155, 138}}
constexpr Knobs g_knobs = DEFAULT_KNOBS;

__device__ unsigned int g_tile_counter;

__device__ __forceinline__ uint32_t smem_u32(const void* p) { return (uint32_t)__cvta_generic_to_shared(p); }

__device__ __forceinline__ void mbar_init(uint32_t bar, uint32_t cnt) {
    asm volatile("mbarrier.init.shared::cta.b64 [%0], %1;" ::"r"(bar), "r"(cnt) : "memory");
}
__device__ __forceinline__ void mbar_expect_tx(uint32_t bar, uint32_t bytes) {
    asm volatile("mbarrier.arrive.expect_tx.shared::cta.b64 _, [%0], %1;" ::"r"(bar), "r"(bytes) : "memory");
}
__device__ __forceinline__ void mbar_arrive(uint32_t bar) {
    asm volatile("mbarrier.arrive.shared::cta.b64 _, [%0];" ::"r"(bar) : "memory");
}
__device__ __forceinline__ void mbar_arrive_cluster(uint32_t bar) {
    asm volatile("mbarrier.arrive.shared::cluster.b64 _, [%0];" ::"r"(bar) : "memory");
}
__device__ __forceinline__ void mbar_wait(uint32_t bar, uint32_t parity) {
    asm volatile(
        "{\n.reg .pred p;\n.reg .u32 n;\n"
        "mbarrier.try_wait.parity.shared::cta.b64 p, [%0], %1;\n"
        "@p bra DONE;\n"
        "mov.u32 n, 0;\n"
        "LOOP:\n"
        "mbarrier.try_wait.parity.shared::cta.b64 p, [%0], %1;\n"
        "@p bra DONE;\n"
        "add.u32 n, n, 1;\n"
        "setp.lt.u32 p, n, 4194304;\n"
        "@p bra LOOP;\n"
        "trap;\n"
        "DONE:\n}" ::"r"(bar), "r"(parity) : "memory");
}
__device__ __forceinline__ uint32_t map_to_cta(uint32_t addr, uint32_t cta) {
    uint32_t r;
    asm("mapa.shared::cluster.u32 %0, %1, %2;" : "=r"(r) : "r"(addr), "r"(cta));
    return r;
}
__device__ __forceinline__ void named_bar_sync(int id, int n) { asm volatile("bar.sync %0, %1;" ::"r"(id), "r"(n) : "memory"); }
__device__ __forceinline__ void named_bar_arrive(int id, int n) { asm volatile("bar.arrive %0, %1;" ::"r"(id), "r"(n) : "memory"); }
__device__ __forceinline__ void cluster_arrive() {
    __syncwarp();
    asm volatile("barrier.cluster.arrive.relaxed.aligned;" ::: "memory");
}
__device__ __forceinline__ void cluster_wait() {
    __syncwarp();
    asm volatile("barrier.cluster.wait.acquire.aligned;" ::: "memory");
}
__device__ __forceinline__ void prefetch_line(const void* p) { asm volatile("prefetch.global.L2 [%0];" ::"l"(p) : "memory"); }
__device__ __forceinline__ void prefetch_map(const CUtensorMap* m) { asm volatile("prefetch.tensormap [%0];" ::"l"(m) : "memory"); }
__device__ __forceinline__ uint32_t globaltimer() {
    uint32_t t;
    asm volatile("mov.u32 %0, %%globaltimer_lo;" : "=r"(t));
    return t;
}
__device__ __forceinline__ uint32_t clock32() {
    uint32_t t;
    asm volatile("mov.u32 %0, %%clock;" : "=r"(t));
    return t;
}
__device__ __forceinline__ int lds32(uint32_t addr) {
    int v;
    asm volatile("ld.shared.b32 %0, [%1];" : "=r"(v) : "r"(addr) : "memory");
    return v;
}
__device__ __forceinline__ int lds32_volatile(uint32_t addr) {
    int v;
    asm volatile("ld.volatile.shared.b32 %0, [%1];" : "=r"(v) : "r"(addr) : "memory");
    return v;
}
__device__ __forceinline__ void sts32(uint32_t addr, int v) { asm volatile("st.shared.b32 [%0], %1;" ::"r"(addr), "r"(v) : "memory"); }

#define ACC4(o) "+f"(d[o]), "+f"(d[o + 1]), "+f"(d[o + 2]), "+f"(d[o + 3])
#define ACC16(o) ACC4(o), ACC4(o + 4), ACC4(o + 8), ACC4(o + 12)
__device__ __forceinline__ void wgmma_rs(float (&d)[32], const uint32_t (&a)[4], uint64_t desc_b, int scale_d) {
    asm volatile(
        "{\n.reg .pred p;\nsetp.ne.b32 p, %37, 0;\n"
        "wgmma.mma_async.sync.aligned.m64n64k16.f32.bf16.bf16 "
        "{%0, %1, %2, %3, %4, %5, %6, %7, %8, %9, %10, %11, %12, %13, %14, %15, "
        "%16, %17, %18, %19, %20, %21, %22, %23, %24, %25, %26, %27, %28, %29, %30, %31}, "
        "{%32, %33, %34, %35}, %36, p, 1, 1, 0;\n}"
        : ACC16(0), ACC16(16)
        : "r"(a[0]), "r"(a[1]), "r"(a[2]), "r"(a[3]), "l"(desc_b), "r"(scale_d));
}
__device__ __forceinline__ void wgmma_rs(float (&d)[16], const uint32_t (&a)[4], uint64_t desc_b, int scale_d) {
    asm volatile(
        "{\n.reg .pred p;\nsetp.ne.b32 p, %21, 0;\n"
        "wgmma.mma_async.sync.aligned.m64n32k16.f32.bf16.bf16 "
        "{%0, %1, %2, %3, %4, %5, %6, %7, %8, %9, %10, %11, %12, %13, %14, %15}, "
        "{%16, %17, %18, %19}, %20, p, 1, 1, 0;\n}"
        : ACC16(0)
        : "r"(a[0]), "r"(a[1]), "r"(a[2]), "r"(a[3]), "l"(desc_b), "r"(scale_d));
}
__device__ __forceinline__ uint64_t make_desc(uint32_t addr, uint32_t group_stride) {
    return (uint64_t(1) << 62) | (uint64_t(group_stride >> 4) << 32) | (uint64_t(1) << 16) | (uint64_t)((addr & 0x3FFFF) >> 4);
}
__device__ __forceinline__ constexpr uint64_t desc_k(int k) { return (uint64_t)(((k >> 2) * 1024 + (k & 3) * 32) >> 4); }

__device__ __forceinline__ uint32_t pack_bf16(float lo, float hi) {
    uint32_t r;
    asm("cvt.rn.bf16x2.f32 %0, %1, %2;" : "=r"(r) : "f"(hi), "f"(lo));
    return r;
}
__device__ __forceinline__ uint32_t mul_bf16x2(uint32_t a, uint32_t b) {
    uint32_t r;
    asm("mul.rn.bf16x2 %0, %1, %2;" : "=r"(r) : "r"(a), "r"(b));
    return r;
}

__global__ void __cluster_dims__(2, 1, 1) __launch_bounds__(kThreads, 1)
dwsep_kernel(const __grid_constant__ CUtensorMap tm_w, const __grid_constant__ CUtensorMap tm_x0,
             const __grid_constant__ CUtensorMap tm_x, const __grid_constant__ CUtensorMap tm_o,
             const __nv_bfloat16* __restrict__ x, const __nv_bfloat16* __restrict__ dw,
             const __nv_bfloat16* __restrict__ pw, int num_tiles, const Knobs kn) {
    extern __shared__ __align__(1024) uint8_t smem_raw[];
    const uint32_t sb = smem_u32(smem_raw);

    uint32_t rank;
    asm("mov.u32 %0, %%cluster_ctarank;" : "=r"(rank));
    const int cluster = blockIdx.x >> 1;
    auto static_tile = [&](int i) { return (i >> 1) * gridDim.x + cluster * 2 + (i & 1); };

    if (threadIdx.x < 32) {
        prefetch_line(threadIdx.x < 18 ? (const char*)pw + (blockIdx.x & 127) * 2304 + threadIdx.x * 128
                                       : (const char*)dw + min(threadIdx.x - 18, 5) * 128);
    } else if (threadIdx.x < 224) {
        const uint32_t c0 = __shfl_sync(0xffffffffu, clock32(), 0), chunk = (threadIdx.x >> 5) - 1;
        const uint32_t delay = ((chunk >> 1) * gridDim.x + blockIdx.x) * kn.first_gap >> 7;
        for (int n = 0; clock32() - c0 < delay && n < 1024; n++) {}
        prefetch_line((const char*)x + (size_t)blockIdx.x * kStageBytes + (threadIdx.x & 31) * 768 + chunk * 128);
    } else if (threadIdx.x == 288) {
        prefetch_map(&tm_w);
        prefetch_map(&tm_x0);
    }
    if (threadIdx.x >> 5 == 8) {
        if (threadIdx.x == 256) {
#pragma unroll
            for (int b = 0; b < 7; b++) mbar_init(sb + kWBarOff + 8 * b, 1);
            asm volatile("fence.proxy.async.shared::cta;" ::: "memory");
        }
        __syncwarp();
        named_bar_arrive(8, 384);
        if (threadIdx.x == 256) {
            mbar_expect_tx(sb + kDwBarOff, kC * 2);
            asm volatile("cp.async.bulk.shared::cluster.global.mbarrier::complete_tx::bytes [%0], [%1], %2, [%3];"
                         ::"r"(sb + kDwOff), "l"(dw), "r"(kC * 2), "r"(sb + kDwBarOff) : "memory");
#pragma unroll
            for (int j = 0; j < 3; j++) {
                mbar_expect_tx(sb + kWBarOff + 8 * j, 2 * kWChunkBytes);
#pragma unroll
                for (int c = 2 * j; c < 2 * j + 2; c++)
                    asm volatile("cp.async.bulk.tensor.3d.shared::cluster.global.mbarrier::complete_tx::bytes [%0], [%1, {%3, %4, %5}], [%2];"
                                 ::"r"(sb + kWOff + c * kWChunkBytes), "l"(&tm_w), "r"(sb + kWBarOff + 8 * j), "r"(0), "r"(c * 64),
                                   "r"((int)rank * 3) : "memory");
                mbar_expect_tx(sb + kXBarOff + 8 * j, kXSlabBytes);
                asm volatile("cp.async.bulk.tensor.4d.shared::cluster.global.mbarrier::complete_tx::bytes [%0], [%1, {%3, %3, %4, %5}], [%2];"
                             ::"r"(sb + j * kXSlabBytes), "l"(&tm_x0), "r"(sb + kXBarOff + 8 * j), "r"(0), "r"(2 * j),
                               "r"(cluster * 8) : "memory");
            }
        }
        __syncwarp();
    }

    if (threadIdx.x < 384) {
        asm volatile("setmaxnreg.inc.sync.aligned.u32 160;");
        cluster_arrive();
        if (threadIdx.x >> 5 != 8) named_bar_sync(8, 384);
        const int wg = __shfl_sync(0xffffffffu, threadIdx.x >> 7, 0);
        const int warp = (threadIdx.x >> 5) & 3;
        const int lane = threadIdx.x & 31;
        const int mi = lane >> 3, ri = lane & 7;
        const uint32_t leader_empty = map_to_cta(sb + kEmptyOff, 0);
        const uint32_t st_off = sb + kOutOff + (((mi >> 1) * 8 + ri) * 3 + wg) * 128 + (((2 * warp + (mi & 1)) ^ ((3 * ri + wg) & 7)) << 4);
        int s = 0, ob = 0;
        uint32_t ph = 0, oph = 1;
        auto release_stage = [&]() {
            if (lane == 0) mbar_arrive_cluster(leader_empty + 8 * s);
            if (++s == kStages) { s = 0; ph ^= 1; }
        };
        auto pack = [&](uint32_t (&p)[8], const float* acc) {
#pragma unroll
            for (int k = 0; k < 8; k++) p[k] = pack_bf16(acc[2 * k], acc[2 * k + 1]);
        };
        auto put = [&](const uint32_t (&p)[8], int t) {
            mbar_wait(sb + kOEmptyOff + 8 * ob, oph);
            if (threadIdx.x == 0) sts32(sb + kOSlotOff + 4 * ob, t);
#pragma unroll
            for (int q = 0; q < 2; q++)
                asm volatile("stmatrix.sync.aligned.m8n8.x4.trans.shared.b16 [%0], {%1, %2, %3, %4};"
                             ::"r"(st_off + ob * kOutBytes + q * (16 * 384)), "r"(p[4 * q]), "r"(p[4 * q + 1]),
                               "r"(p[4 * q + 2]), "r"(p[4 * q + 3]) : "memory");
            asm volatile("fence.proxy.async.shared::cta;" ::: "memory");
            __syncwarp();
            if (lane == 0) mbar_arrive(sb + kOFullOff + 8 * ob);
            if (++ob == kOutBufs) { ob = 0; oph ^= 1; }
        };
        auto my_turn = [&]() { named_bar_sync(2 + wg, 256); };
        auto pass_turn = [&]() { named_bar_arrive(wg == 2 ? 2 : 3 + wg, 256); };
        if (wg == 2) pass_turn();

        uint32_t a[24][4];
        {
            float acc0[32];
            uint32_t dws[48];
            mbar_wait(sb + kDwBarOff, 0);
#pragma unroll
            for (int k = 0; k < 48; k++) dws[k] = lds32(sb + kDwOff + k * 16 + (lane & 3) * 4);
            cluster_wait();
            if (lane < 2) mbar_arrive_cluster(leader_empty + 8 * lane);
            const uint32_t wbase = sb + kWOff + wg * 8192 + ((mi >> 1) * 8 + ri) * 128 + (((2 * warp + (mi & 1)) ^ ri) << 4);
            const uint64_t desc = make_desc(sb, 2048);
#pragma unroll
            for (int j = 0; j < 3; j++) {
                mbar_wait(sb + kWBarOff + 8 * j, 0);
#pragma unroll
                for (int k = 8 * j; k < 8 * j + 8; k++) {
                    asm volatile("ldmatrix.sync.aligned.m8n8.x4.trans.shared.b16 {%0, %1, %2, %3}, [%4];"
                                 : "=r"(a[k][0]), "=r"(a[k][1]), "=r"(a[k][2]), "=r"(a[k][3])
                                 : "r"(wbase + (k >> 2) * kWChunkBytes + (k & 3) * 2048) : "memory");
                    a[k][0] = mul_bf16x2(a[k][0], dws[2 * k]);
                    a[k][1] = mul_bf16x2(a[k][1], dws[2 * k]);
                    a[k][2] = mul_bf16x2(a[k][2], dws[2 * k + 1]);
                    a[k][3] = mul_bf16x2(a[k][3], dws[2 * k + 1]);
                }
                uint32_t dep = 0;
#pragma unroll
                for (int k = 8 * j; k < 8 * j + 8; k++) dep ^= a[k][3];
                dep &= num_tiles >> 24;
                if (lane >> 1 == j + 1 && lane < kStages) mbar_arrive_cluster(leader_empty + 8 * lane + dep);
                if (j == 2) {
                    named_bar_arrive(wg == 0 ? 6 : 5, 384);
                    named_bar_arrive(wg == 2 ? 6 : 7, 384);
                }
                mbar_wait(sb + kXBarOff + 8 * j, 0);
                my_turn();
                asm volatile("wgmma.fence.sync.aligned;" ::: "memory");
#pragma unroll
                for (int k = 0; k < 8; k++) wgmma_rs(acc0, a[8 * j + k], desc + (j * kXSlabBytes >> 4) + desc_k(k), j + k != 0);
                pass_turn();
            }
            asm volatile("wgmma.commit_group.sync.aligned;" ::: "memory");
            named_bar_sync(5 + wg, 384);
            asm volatile("wgmma.wait_group.sync.aligned 0;" ::: "memory");
            release_stage();
            release_stage();
            uint32_t p[8];
            pack(p, acc0);
            put(p, static_tile(0));
            pack(p, acc0 + 16);
            put(p, static_tile(1));
        }

        float acc[16];
        uint32_t park[kPark][8], park_last;
        int parked = 0;
        auto spill_addr = [&](int base, int shift) { return sb + kSpillOff + base + ((st_off - sb - kOutOff) >> shift); };
        asm volatile("mov.b32 %0, 0;" : "=r"(park_last));
#pragma unroll
        for (int k = 0; k < kPark * 8; k++) asm volatile("mov.b32 %0, 0;" : "=r"(park[k / 8][k % 8]));
#pragma unroll 1
        while (true) {
            mbar_wait(sb + kFullOff + 8 * s, ph);
            const int t = lds32(sb + kSlotOff + 4 * s);
            if (t >= num_tiles) break;
            const uint64_t desc = make_desc(sb + s * kStageBytes, 6144);
            my_turn();
            asm volatile("wgmma.fence.sync.aligned;" ::: "memory");
#pragma unroll
            for (int k = 0; k < 24; k++) {
                if (k == 20) pass_turn();
                wgmma_rs(acc, a[k], desc + desc_k(k), k != 0);
            }
            asm volatile("wgmma.commit_group.sync.aligned;" ::: "memory");
            asm volatile("wgmma.wait_group.sync.aligned 0;" ::: "memory");
            release_stage();
            const int keep = t >= kn.park_from ? kPark + 1 : t >= kn.mid_from && t < kn.mid_to ? kn.mid_n : 0;
            if (parked < keep) {
#pragma unroll
                for (int k = 0; k < kPark; k++)
                    if (parked == k) pack(park[k], acc);
                if (parked == kPark) {
                    uint32_t p[8];
                    pack(p, acc);
                    asm volatile("st.shared.v4.b32 [%0], {%1, %2, %3, %4};"
                                 ::"r"(spill_addr(0, 0)), "r"(p[0]), "r"(p[1]), "r"(p[2]), "r"(p[3]) : "memory");
                    asm volatile("st.shared.v2.b32 [%0], {%1, %2};" ::"r"(spill_addr(6144, 1)), "r"(p[4]), "r"(p[5]) : "memory");
                    sts32(spill_addr(9216, 2), p[6]);
                    asm volatile("xor.b32 %0, %1, %2;" : "=r"(park_last) : "r"(p[7]), "r"(st_off));
                }
                if (threadIdx.x == 0) sts32(sb + kPSlotOff + 4 * parked, t);
                parked++;
            } else {
                uint32_t p[8];
                pack(p, acc);
                put(p, t);
                if (parked > keep) {
#pragma unroll
                    for (int k = 2; k >= 0; k--)
                        if (k < parked) put(park[k], threadIdx.x == 0 ? lds32(sb + kPSlotOff + 4 * k) : 0);
                    parked = 0;
                }
            }
        }
#pragma unroll
        for (int k = 0; k < kPark; k++)
            if (k < parked) put(park[k], threadIdx.x == 0 ? lds32(sb + kPSlotOff + 4 * k) : 0);
        if (parked > kPark) {
            uint32_t p[8];
            asm volatile("ld.shared.v4.b32 {%0, %1, %2, %3}, [%4];"
                         : "=r"(p[0]), "=r"(p[1]), "=r"(p[2]), "=r"(p[3]) : "r"(spill_addr(0, 0)) : "memory");
            asm volatile("ld.shared.v2.b32 {%0, %1}, [%2];" : "=r"(p[4]), "=r"(p[5]) : "r"(spill_addr(6144, 1)) : "memory");
            p[6] = lds32(spill_addr(9216, 2));
            asm volatile("xor.b32 %0, %1, %2;" : "=r"(p[7]) : "r"(park_last), "r"(st_off));
            put(p, threadIdx.x == 0 ? lds32(sb + kPSlotOff + 4 * kPark) : 0);
        }
#pragma unroll 1
        for (int k = 0; k < 2; k++) {
            mbar_wait(sb + kOEmptyOff + 8 * ob, oph);
            if (threadIdx.x == 0) sts32(sb + kOSlotOff + 4 * ob, num_tiles);
            if (lane == 0) mbar_arrive(sb + kOFullOff + 8 * ob);
            if (++ob == kOutBufs) { ob = 0; oph ^= 1; }
        }
    } else {
        asm volatile("setmaxnreg.dec.sync.aligned.u32 32;");
        const int role = (threadIdx.x >> 5) & 3;
        const bool lead = (threadIdx.x & 31) == 0;
        if (role >= 2) {
            const int par = role & 1;
            if (lead) {
                if (par == 0) {
#pragma unroll
                    for (int b = 0; b < kOutBufs; b++) {
                        mbar_init(sb + kOFullOff + 8 * b, 12);
                        mbar_init(sb + kOEmptyOff + 8 * b, 1);
                    }
                } else {
#pragma unroll
                    for (int s = 0; s < kStages; s++) {
                        mbar_init(sb + kFullOff + 8 * s, 1);
                        mbar_init(sb + kEmptyOff + 8 * s, 24);
                        if (s < 2) mbar_arrive(sb + kFullOff + 8 * s);
                    }
                    prefetch_map(&tm_x);
                    prefetch_map(&tm_o);
                }
                asm volatile("fence.mbarrier_init.release.cluster;" ::: "memory");
            }
            cluster_arrive();
            cluster_wait();
            if (lead) {
                uint64_t policy;
                asm volatile("createpolicy.fractional.L2::evict_normal.b64 %0, 1.0;" : "=l"(policy));
                int head = par, tail = par, freed = par, held = 0, busy = 0, pos = 0;
                uint32_t ph = 0;
#pragma unroll 1
                while (true) {
                    mbar_wait(sb + kOFullOff + 8 * head, ph);
                    const int t = lds32(sb + kOSlotOff + 4 * head);
                    int hold = 0, lag = 0;
                    if (t < num_tiles) {
                        held++;
                        pos = max(pos, t);
                        if ((head += 2) >= kOutBufs) { head = par; ph ^= 1; }
#pragma unroll
                        for (int k = 0; k < 6; k++)
                            if (pos >= kn.hold_pos[k]) hold = kn.hold[k];
                        if (pos >= kn.park_from) lag = min(kn.lag, 3 - hold);
                        if (pos >= kn.stream_from) asm volatile("createpolicy.fractional.L2::evict_first.b64 %0, 1.0;" : "=l"(policy));
                    }
#pragma unroll 1
                    for (; held > hold; held--, busy++) {
                        asm volatile("cp.async.bulk.tensor.3d.global.shared::cta.bulk_group.L2::cache_hint [%0, {%2, %3, %4}], [%1], %5;"
                                     ::"l"(&tm_o), "r"(sb + kOutOff + tail * kOutBytes), "r"(0), "r"((int)rank * 3),
                                       "r"(lds32(sb + kOSlotOff + 4 * tail) * kTilePx), "l"(policy) : "memory");
                        asm volatile("cp.async.bulk.commit_group;" ::: "memory");
                        if ((tail += 2) >= kOutBufs) tail = par;
                    }
#pragma unroll 1
                    while (busy > lag) {
                        busy--;
                        if (busy == 0) asm volatile("cp.async.bulk.wait_group.read 0;" ::: "memory");
                        else if (busy == 1) asm volatile("cp.async.bulk.wait_group.read 1;" ::: "memory");
                        else if (busy == 2) asm volatile("cp.async.bulk.wait_group.read 2;" ::: "memory");
                        else asm volatile("cp.async.bulk.wait_group.read 3;" ::: "memory");
                        mbar_arrive(sb + kOEmptyOff + 8 * freed);
                        if ((freed += 2) >= kOutBufs) freed = par;
                    }
                    if (t >= num_tiles) break;
                }
            }
        } else if (role == 1) {
            const uint32_t t_start = __shfl_sync(0xffffffffu, globaltimer(), 0);
            const uint32_t my_slot = sb + kSlotOff + 4 * min(threadIdx.x & 31, kStages - 1);
            sts32(my_slot, 0);
            __threadfence_block();
            cluster_arrive();
#pragma unroll 1
            for (int t = blockIdx.x + gridDim.x; t < num_tiles; t += gridDim.x) {
                const uint32_t due = kn.pf_t0 + (t - gridDim.x) * kn.pf_dt / gridDim.x;
                for (int n = 0; globaltimer() - t_start < due && n < 4096; n++) __nanosleep(50);
                int p0 = 0, l0 = kn.lead[0], slope = 0;
#pragma unroll
                for (int k = 0; k < 8; k++)
                    if (t >= kn.lead_pos[k]) { p0 = kn.lead_pos[k]; l0 = kn.lead[k]; slope = kn.lead_slope[k]; }
                const int max_lead = l0 + ((t - p0) * slope >> 16);
                for (int n = 0; t > max_lead && n < 4096; n++) {
                    const int front = __reduce_max_sync(0xffffffffu, lds32_volatile(my_slot));
                    if (t - max_lead <= front || front >= num_tiles) break;
                    __nanosleep(50);
                }
                const char* src = (const char*)x + (size_t)t * kStageBytes;
                if (t < kn.pull_to) {
#pragma unroll
                    for (int j = 0; j < 6; j++)
                        asm volatile("cp.async.ca.shared.global.L2::128B [%0], [%1], 4;"
                                     ::"r"(sb + kScratchOff + (threadIdx.x & 31) * 4 + j * (num_tiles >> 24)),
                                       "l"(src + (j * 32 + (threadIdx.x & 31)) * 128) : "memory");
                } else if (lead) {
                    asm volatile("cp.async.bulk.prefetch.L2.global [%0], %1;" ::"l"(src), "r"(kStageBytes) : "memory");
                }
            }
            asm volatile("cp.async.wait_all;" ::: "memory");
            cluster_wait();
        } else {
            cluster_arrive();
            cluster_wait();
            if (lead && rank == 0) {
                const uint32_t peer = map_to_cta(sb, 1);
                const int nstatic = kn.static_tiles * (gridDim.x >> 1);
                const unsigned last_fetch = num_tiles - nstatic + gridDim.x - 1;
                mbar_wait(sb + kEmptyOff, 0);
                mbar_wait(sb + kEmptyOff + 8, 0);
                int s = 2, i = 2;
                uint32_t ph = 0;
                auto step = [&](unsigned& raw) -> bool {
                    const int t = nstatic + raw;
                    const bool valid = t < num_tiles;
                    raw = static_tile(i + 2) - nstatic;
                    if (i + 2 >= kn.static_tiles && valid)
                        asm volatile("atom.global.inc.u32 %0, [%1], %2;" : "+r"(raw) : "l"(&g_tile_counter), "r"(last_fetch) : "memory");
                    mbar_wait(sb + kEmptyOff + 8 * s, ph);
                    const uint32_t full = kFullOff + 8 * s, slot = kSlotOff + 4 * s;
                    const uint32_t bytes = valid ? kStageBytes : 0;
                    sts32(sb + slot, t);
                    mbar_expect_tx(sb + full, bytes);
                    asm volatile("mbarrier.arrive.expect_tx.shared::cluster.b64 _, [%0], %1;" ::"r"(peer + full), "r"(bytes + 4) : "memory");
                    asm volatile("st.async.weak.shared::cluster.mbarrier::complete_tx::bytes.b32 [%0], %1, [%2];"
                                 ::"r"(peer + slot), "r"(t), "r"(peer + full) : "memory");
                    if (!valid) return false;
                    asm volatile(
                        "cp.async.bulk.tensor.4d.shared::cluster.global.mbarrier::complete_tx::bytes.multicast::cluster "
                        "[%0], [%1, {%3, %3, %3, %4}], [%2], %5;"
                        ::"r"(sb + s * kStageBytes), "l"(&tm_x), "r"(sb + full), "r"(0), "r"(t * (kTilePx / 8)),
                          "h"((uint16_t)3) : "memory");
                    if (++s == kStages) { s = 0; ph ^= 1; }
                    i++;
                    return true;
                };
                unsigned raw0 = static_tile(2) - nstatic, raw1 = static_tile(3) - nstatic;
#pragma unroll 1
                while (step(raw0) && step(raw1)) {}
#pragma unroll 1
                for (int k = 1; k < kStages; k++) {
                    if (++s == kStages) { s = 0; ph ^= 1; }
                    mbar_wait(sb + kEmptyOff + 8 * s, ph);
                }
            }
        }
    }
}

typedef CUresult (*EncodeTiledFn)(CUtensorMap*, CUtensorMapDataType, cuuint32_t, void*, const cuuint64_t*,
                                  const cuuint64_t*, const cuuint32_t*, const cuuint32_t*, CUtensorMapInterleave,
                                  CUtensorMapSwizzle, CUtensorMapL2promotion, CUtensorMapFloatOOBfill);

}

extern "C" void kernel_launch(void* const* d_in, const int* in_sizes, int n_in, void* d_out, int out_size) {
    (void)n_in; (void)out_size;
    const __nv_bfloat16* x = (const __nv_bfloat16*)d_in[0];
    const __nv_bfloat16* dw = (const __nv_bfloat16*)d_in[1];
    const __nv_bfloat16* pw = (const __nv_bfloat16*)d_in[2];
    const int pixels = in_sizes[0] / kC;

    static EncodeTiledFn encode = nullptr;
    static int grid = 0;
    if (!encode) {
        void* fn = nullptr;
        cudaDriverEntryPointQueryResult qr;
        cudaGetDriverEntryPoint("cuTensorMapEncodeTiled", &fn, cudaEnableDefault, &qr);
        encode = (EncodeTiledFn)fn;
        cudaFuncSetAttribute(dwsep_kernel, cudaFuncAttributeMaxDynamicSharedMemorySize, kSmemBytes);
        int sms = 0, clusters = 0;
        cudaDeviceGetAttribute(&sms, cudaDevAttrMultiProcessorCount, 0);
        cudaLaunchConfig_t cfg = {};
        cudaLaunchAttribute attr = {};
        attr.id = cudaLaunchAttributeClusterDimension;
        attr.val.clusterDim.x = 2;
        attr.val.clusterDim.y = attr.val.clusterDim.z = 1;
        cfg.gridDim = dim3(sms & ~1);
        cfg.blockDim = dim3(kThreads);
        cfg.dynamicSmemBytes = kSmemBytes;
        cfg.attrs = &attr;
        cfg.numAttrs = 1;
        if (cudaOccupancyMaxActiveClusters(&clusters, dwsep_kernel, &cfg) != cudaSuccess || clusters < 1) {
            (void)cudaGetLastError();
            clusters = sms / 2;
        }
        grid = 2 * (clusters < sms / 2 ? clusters : sms / 2);
    }

    CUtensorMap tm_w, tm_x0, tm_x, tm_o;
    auto make_map = [&](CUtensorMap* m, const void* base, int rank, const cuuint64_t* dims, const cuuint64_t* strides,
                        const cuuint32_t* box, CUtensorMapL2promotion promo) {
        const cuuint32_t ones[4] = {1, 1, 1, 1};
        encode(m, CU_TENSOR_MAP_DATA_TYPE_BFLOAT16, rank, (void*)base, dims, strides, box, ones,
               CU_TENSOR_MAP_INTERLEAVE_NONE, CU_TENSOR_MAP_SWIZZLE_128B, promo, CU_TENSOR_MAP_FLOAT_OOB_FILL_NONE);
    };
    {
        const cuuint64_t dims[3] = {64, kC, 6}, strides[2] = {kC * 2, 128};
        const cuuint32_t box[3] = {64, 64, 3};
        make_map(&tm_w, pw, 3, dims, strides, box, CU_TENSOR_MAP_L2_PROMOTION_L2_128B);
    }
    {
        const cuuint64_t dims[4] = {64, 8, 6, (cuuint64_t)pixels / 8}, strides[3] = {kC * 2, 128, kC * 2 * 8};
        const cuuint32_t box0[4] = {64, 8, 2, 8}, box[4] = {64, 8, 6, kTilePx / 8};
        make_map(&tm_x0, x, 4, dims, strides, box0, CU_TENSOR_MAP_L2_PROMOTION_L2_128B);
        make_map(&tm_x, x, 4, dims, strides, box, CU_TENSOR_MAP_L2_PROMOTION_L2_128B);
    }
    {
        const cuuint64_t dims[3] = {64, 6, (cuuint64_t)pixels}, strides[2] = {128, kC * 2};
        const cuuint32_t box[3] = {64, 3, kTilePx};
        make_map(&tm_o, d_out, 3, dims, strides, box, CU_TENSOR_MAP_L2_PROMOTION_NONE);
    }
    Knobs kn = g_knobs;
    for (int k = 0; k < 8; k++)
        kn.lead_slope[k] = k < 7 ? (kn.lead[k + 1] - kn.lead[k]) * 65536 / (kn.lead_pos[k + 1] - kn.lead_pos[k]) : 0;
    dwsep_kernel<<<grid, kThreads, kSmemBytes, cudaStreamPerThread>>>(tm_w, tm_x0, tm_x, tm_o, x, dw, pw,
                                                                      pixels / kTilePx, kn);
}
```

```cpp
#include <cuda_runtime.h>
#include <cuda_bf16.h>
#include <cuda.h>
#include <stdint.h>

namespace {

constexpr int kC = 384;
constexpr int kTilePx = 32;
constexpr int kStages = 5;
constexpr int kOutBufs = 8;
constexpr int kPark = 5;
constexpr int kThreads = 512;
constexpr int kStageBytes = kTilePx * kC * 2;
constexpr int kOutBytes = kTilePx * 192 * 2;
constexpr int kWChunkBytes = 64 * 192 * 2;
constexpr int kXSlabBytes = 64 * 128 * 2;
constexpr int kWOff = 2 * kStageBytes;
constexpr int kOutOff = kStages * kStageBytes;
constexpr int kSpillOff = kOutOff + kOutBufs * kOutBytes;
constexpr int kDwOff = kSpillOff;
constexpr int kFullOff = kSpillOff + 384 * 28;
constexpr int kEmptyOff = kFullOff + 8 * kStages;
constexpr int kOFullOff = kEmptyOff + 8 * kStages;
constexpr int kOEmptyOff = kOFullOff + 8 * kOutBufs;
constexpr int kWBarOff = kOEmptyOff + 8 * kOutBufs;
constexpr int kXBarOff = kWBarOff + 8 * 3;
constexpr int kDwBarOff = kXBarOff + 8 * 3;
constexpr int kSlotOff = kDwBarOff + 8;
constexpr int kOSlotOff = kSlotOff + 4 * kStages;
constexpr int kPSlotOff = kOSlotOff + 4 * kOutBufs;
constexpr int kScratchOff = kPSlotOff + 4 * (kPark + 1);
constexpr int kSmemBytes = kScratchOff + 128;
static_assert(kWChunkBytes == kStageBytes && kWOff + 6 * kWChunkBytes <= kDwOff, "weight staging");
static_assert(kSmemBytes <= 232448, "shared memory");

struct Knobs {
    int first_gap;
    int pf_t0, pf_dt;
    int pull_to;
    int static_tiles;
    int mid_from, mid_to, mid_n;
    int park_from;
    int stream_from;
    int lag;
    int hold_pos[6], hold[6];
    int lead_pos[8], lead[8];
    int lead_slope[8];
};
#define DEFAULT_KNOBS {514, 280, 840, 528, 18, 1810, 2600, 2, 3430, 4420, 2, \
    {0, 440, 721, 1081, 4260, 4608}, {0, 1, 2, 3, 1, 1}, \
    {845, 1485, 1890, 2220, 2245, 3442, 4120, 4500}, {380, 543, 350, 314, 350, 84, 155, 138}}
constexpr Knobs g_knobs = DEFAULT_KNOBS;

__device__ unsigned int g_tile_counter;

__device__ __forceinline__ uint32_t smem_u32(const void* p) { return (uint32_t)__cvta_generic_to_shared(p); }

__device__ __forceinline__ void mbar_init(uint32_t bar, uint32_t cnt) {
    asm volatile("mbarrier.init.shared::cta.b64 [%0], %1;" ::"r"(bar), "r"(cnt) : "memory");
}
__device__ __forceinline__ void mbar_expect_tx(uint32_t bar, uint32_t bytes) {
    asm volatile("mbarrier.arrive.expect_tx.shared::cta.b64 _, [%0], %1;" ::"r"(bar), "r"(bytes) : "memory");
}
__device__ __forceinline__ void mbar_arrive(uint32_t bar) {
    asm volatile("mbarrier.arrive.shared::cta.b64 _, [%0];" ::"r"(bar) : "memory");
}
__device__ __forceinline__ void mbar_arrive_cluster(uint32_t bar) {
    asm volatile("mbarrier.arrive.shared::cluster.b64 _, [%0];" ::"r"(bar) : "memory");
}
__device__ __forceinline__ void mbar_wait(uint32_t bar, uint32_t parity) {
    asm volatile(
        "{\n.reg .pred p;\n.reg .u32 n;\n"
        "mbarrier.try_wait.parity.shared::cta.b64 p, [%0], %1;\n"
        "@p bra DONE;\n"
        "mov.u32 n, 0;\n"
        "LOOP:\n"
        "mbarrier.try_wait.parity.shared::cta.b64 p, [%0], %1;\n"
        "@p bra DONE;\n"
        "add.u32 n, n, 1;\n"
        "setp.lt.u32 p, n, 4194304;\n"
        "@p bra LOOP;\n"
        "trap;\n"
        "DONE:\n}" ::"r"(bar), "r"(parity) : "memory");
}
__device__ __forceinline__ uint32_t map_to_cta(uint32_t addr, uint32_t cta) {
    uint32_t r;
    asm("mapa.shared::cluster.u32 %0, %1, %2;" : "=r"(r) : "r"(addr), "r"(cta));
    return r;
}
__device__ __forceinline__ void named_bar_sync(int id, int n) { asm volatile("bar.sync %0, %1;" ::"r"(id), "r"(n) : "memory"); }
__device__ __forceinline__ void named_bar_arrive(int id, int n) { asm volatile("bar.arrive %0, %1;" ::"r"(id), "r"(n) : "memory"); }
__device__ __forceinline__ void cluster_arrive() {
    __syncwarp();
    asm volatile("barrier.cluster.arrive.relaxed.aligned;" ::: "memory");
}
__device__ __forceinline__ void cluster_wait() {
    __syncwarp();
    asm volatile("barrier.cluster.wait.acquire.aligned;" ::: "memory");
}
__device__ __forceinline__ void prefetch_line(const void* p) { asm volatile("prefetch.global.L2 [%0];" ::"l"(p) : "memory"); }
__device__ __forceinline__ void prefetch_map(const CUtensorMap* m) { asm volatile("prefetch.tensormap [%0];" ::"l"(m) : "memory"); }
__device__ __forceinline__ uint32_t globaltimer() {
    uint32_t t;
    asm volatile("mov.u32 %0, %%globaltimer_lo;" : "=r"(t));
    return t;
}
__device__ __forceinline__ uint32_t clock32() {
    uint32_t t;
    asm volatile("mov.u32 %0, %%clock;" : "=r"(t));
    return t;
}
__device__ __forceinline__ int lds32(uint32_t addr) {
    int v;
    asm volatile("ld.shared.b32 %0, [%1];" : "=r"(v) : "r"(addr) : "memory");
    return v;
}
__device__ __forceinline__ int lds32_volatile(uint32_t addr) {
    int v;
    asm volatile("ld.volatile.shared.b32 %0, [%1];" : "=r"(v) : "r"(addr) : "memory");
    return v;
}
__device__ __forceinline__ void sts32(uint32_t addr, int v) { asm volatile("st.shared.b32 [%0], %1;" ::"r"(addr), "r"(v) : "memory"); }

#define ACC4(o) "+f"(d[o]), "+f"(d[o + 1]), "+f"(d[o + 2]), "+f"(d[o + 3])
#define ACC16(o) ACC4(o), ACC4(o + 4), ACC4(o + 8), ACC4(o + 12)
__device__ __forceinline__ void wgmma_rs(float (&d)[32], const uint32_t (&a)[4], uint64_t desc_b, int scale_d) {
    asm volatile(
        "{\n.reg .pred p;\nsetp.ne.b32 p, %37, 0;\n"
        "wgmma.mma_async.sync.aligned.m64n64k16.f32.bf16.bf16 "
        "{%0, %1, %2, %3, %4, %5, %6, %7, %8, %9, %10, %11, %12, %13, %14, %15, "
        "%16, %17, %18, %19, %20, %21, %22, %23, %24, %25, %26, %27, %28, %29, %30, %31}, "
        "{%32, %33, %34, %35}, %36, p, 1, 1, 0;\n}"
        : ACC16(0), ACC16(16)
        : "r"(a[0]), "r"(a[1]), "r"(a[2]), "r"(a[3]), "l"(desc_b), "r"(scale_d));
}
__device__ __forceinline__ void wgmma_rs(float (&d)[16], const uint32_t (&a)[4], uint64_t desc_b, int scale_d) {
    asm volatile(
        "{\n.reg .pred p;\nsetp.ne.b32 p, %21, 0;\n"
        "wgmma.mma_async.sync.aligned.m64n32k16.f32.bf16.bf16 "
        "{%0, %1, %2, %3, %4, %5, %6, %7, %8, %9, %10, %11, %12, %13, %14, %15}, "
        "{%16, %17, %18, %19}, %20, p, 1, 1, 0;\n}"
        : ACC16(0)
        : "r"(a[0]), "r"(a[1]), "r"(a[2]), "r"(a[3]), "l"(desc_b), "r"(scale_d));
}
__device__ __forceinline__ uint64_t make_desc(uint32_t addr, uint32_t group_stride) {
    return (uint64_t(1) << 62) | (uint64_t(group_stride >> 4) << 32) | (uint64_t(1) << 16) | (uint64_t)((addr & 0x3FFFF) >> 4);
}
__device__ __forceinline__ constexpr uint64_t desc_k(int k) { return (uint64_t)(((k >> 2) * 1024 + (k & 3) * 32) >> 4); }

__device__ __forceinline__ uint32_t pack_bf16(float lo, float hi) {
    uint32_t r;
    asm("cvt.rn.bf16x2.f32 %0, %1, %2;" : "=r"(r) : "f"(hi), "f"(lo));
    return r;
}
__device__ __forceinline__ uint32_t mul_bf16x2(uint32_t a, uint32_t b) {
    uint32_t r;
    asm("mul.rn.bf16x2 %0, %1, %2;" : "=r"(r) : "r"(a), "r"(b));
    return r;
}

__global__ void __cluster_dims__(2, 1, 1) __launch_bounds__(kThreads, 1)
dwsep_kernel(const __grid_constant__ CUtensorMap tm_w, const __grid_constant__ CUtensorMap tm_x0,
             const __grid_constant__ CUtensorMap tm_x, const __grid_constant__ CUtensorMap tm_o,
             const __nv_bfloat16* __restrict__ x, const __nv_bfloat16* __restrict__ dw,
             const __nv_bfloat16* __restrict__ pw, int num_tiles, const Knobs kn) {
    extern __shared__ __align__(1024) uint8_t smem_raw[];
    const uint32_t sb = smem_u32(smem_raw);

    uint32_t rank;
    asm("mov.u32 %0, %%cluster_ctarank;" : "=r"(rank));
    const int cluster = blockIdx.x >> 1;
    auto static_tile = [&](int i) { return (i >> 1) * gridDim.x + cluster * 2 + (i & 1); };

    if (threadIdx.x < 32) {
        prefetch_line(threadIdx.x < 18 ? (const char*)pw + (blockIdx.x & 127) * 2304 + threadIdx.x * 128
                                       : (const char*)dw + min(threadIdx.x - 18, 5) * 128);
    } else if (threadIdx.x < 224) {
        const uint32_t c0 = __shfl_sync(0xffffffffu, clock32(), 0), chunk = (threadIdx.x >> 5) - 1;
        const uint32_t delay = ((chunk >> 1) * gridDim.x + blockIdx.x) * kn.first_gap >> 7;
        for (int n = 0; clock32() - c0 < delay && n < 1024; n++) {}
        prefetch_line((const char*)x + (size_t)blockIdx.x * kStageBytes + (threadIdx.x & 31) * 768 + chunk * 128);
    } else if (threadIdx.x == 288) {
        prefetch_map(&tm_w);
        prefetch_map(&tm_x0);
    }
    if (threadIdx.x >> 5 == 8) {
        if (threadIdx.x == 256) {
#pragma unroll
            for (int b = 0; b < 7; b++) mbar_init(sb + kWBarOff + 8 * b, 1);
            asm volatile("fence.proxy.async.shared::cta;" ::: "memory");
        }
        __syncwarp();
        named_bar_arrive(8, 384);
        if (threadIdx.x == 256) {
            mbar_expect_tx(sb + kDwBarOff, kC * 2);
            asm volatile("cp.async.bulk.shared::cluster.global.mbarrier::complete_tx::bytes [%0], [%1], %2, [%3];"
                         ::"r"(sb + kDwOff), "l"(dw), "r"(kC * 2), "r"(sb + kDwBarOff) : "memory");
#pragma unroll
            for (int j = 0; j < 3; j++) {
                mbar_expect_tx(sb + kWBarOff + 8 * j, 2 * kWChunkBytes);
#pragma unroll
                for (int c = 2 * j; c < 2 * j + 2; c++)
                    asm volatile("cp.async.bulk.tensor.3d.shared::cluster.global.mbarrier::complete_tx::bytes [%0], [%1, {%3, %4, %5}], [%2];"
                                 ::"r"(sb + kWOff + c * kWChunkBytes), "l"(&tm_w), "r"(sb + kWBarOff + 8 * j), "r"(0), "r"(c * 64),
                                   "r"((int)rank * 3) : "memory");
                mbar_expect_tx(sb + kXBarOff + 8 * j, kXSlabBytes);
                asm volatile("cp.async.bulk.tensor.4d.shared::cluster.global.mbarrier::complete_tx::bytes [%0], [%1, {%3, %3, %4, %5}], [%2];"
                             ::"r"(sb + j * kXSlabBytes), "l"(&tm_x0), "r"(sb + kXBarOff + 8 * j), "r"(0), "r"(2 * j),
                               "r"(cluster * 8) : "memory");
            }
        }
        __syncwarp();
    }

    if (threadIdx.x < 384) {
        asm volatile("setmaxnreg.inc.sync.aligned.u32 160;");
        cluster_arrive();
        if (threadIdx.x >> 5 != 8) named_bar_sync(8, 384);
        const int wg = __shfl_sync(0xffffffffu, threadIdx.x >> 7, 0);
        const int warp = (threadIdx.x >> 5) & 3;
        const int lane = threadIdx.x & 31;
        const int mi = lane >> 3, ri = lane & 7;
        const uint32_t leader_empty = map_to_cta(sb + kEmptyOff, 0);
        uint32_t st_off = sb + kOutOff + (((mi >> 1) * 8 + ri) * 3 + wg) * 128 + (((2 * warp + (mi & 1)) ^ ((3 * ri + wg) & 7)) << 4);
        int s = 0, ob = 0;
        uint32_t ph = 0, oph = 1;
        auto release_stage = [&]() {
            if (lane == 0) mbar_arrive_cluster(leader_empty + 8 * s);
            if (++s == kStages) { s = 0; ph ^= 1; }
        };
        auto pack = [&](uint32_t (&p)[8], const float* acc) {
#pragma unroll
            for (int k = 0; k < 8; k++) p[k] = pack_bf16(acc[2 * k], acc[2 * k + 1]);
        };
        auto put = [&](const uint32_t (&p)[8], int t) {
            mbar_wait(sb + kOEmptyOff + 8 * ob, oph);
            if (threadIdx.x == 0) sts32(sb + kOSlotOff + 4 * ob, t);
#pragma unroll
            for (int q = 0; q < 2; q++)
                asm volatile("stmatrix.sync.aligned.m8n8.x4.trans.shared.b16 [%0], {%1, %2, %3, %4};"
                             ::"r"(st_off + ob * kOutBytes + q * (16 * 384)), "r"(p[4 * q]), "r"(p[4 * q + 1]),
                               "r"(p[4 * q + 2]), "r"(p[4 * q + 3]) : "memory");
            asm volatile("fence.proxy.async.shared::cta;" ::: "memory");
            __syncwarp();
            if (lane == 0) mbar_arrive(sb + kOFullOff + 8 * ob);
            if (++ob == kOutBufs) { ob = 0; oph ^= 1; }
        };
        auto my_turn = [&]() { named_bar_sync(2 + wg, 256); };
        auto pass_turn = [&]() { named_bar_arrive(wg == 2 ? 2 : 3 + wg, 256); };
        if (wg == 2) pass_turn();

        uint32_t a[24][4];
        {
            float acc0[32];
            uint32_t dws[48];
            mbar_wait(sb + kDwBarOff, 0);
#pragma unroll
            for (int k = 0; k < 48; k++) dws[k] = lds32(sb + kDwOff + k * 16 + (lane & 3) * 4);
            cluster_wait();
            if (lane < 2) mbar_arrive_cluster(leader_empty + 8 * lane);
            const uint32_t wbase = sb + kWOff + wg * 8192 + ((mi >> 1) * 8 + ri) * 128 + (((2 * warp + (mi & 1)) ^ ri) << 4);
            const uint64_t desc = make_desc(sb, 2048);
#pragma unroll
            for (int j = 0; j < 3; j++) {
                mbar_wait(sb + kWBarOff + 8 * j, 0);
#pragma unroll
                for (int k = 8 * j; k < 8 * j + 8; k++) {
                    asm volatile("ldmatrix.sync.aligned.m8n8.x4.trans.shared.b16 {%0, %1, %2, %3}, [%4];"
                                 : "=r"(a[k][0]), "=r"(a[k][1]), "=r"(a[k][2]), "=r"(a[k][3])
                                 : "r"(wbase + (k >> 2) * kWChunkBytes + (k & 3) * 2048) : "memory");
                    a[k][0] = mul_bf16x2(a[k][0], dws[2 * k]);
                    a[k][1] = mul_bf16x2(a[k][1], dws[2 * k]);
                    a[k][2] = mul_bf16x2(a[k][2], dws[2 * k + 1]);
                    a[k][3] = mul_bf16x2(a[k][3], dws[2 * k + 1]);
                }
                uint32_t dep = 0;
#pragma unroll
                for (int k = 8 * j; k < 8 * j + 8; k++) dep ^= a[k][3];
                dep &= num_tiles >> 24;
                if (lane >> 1 == j + 1 && lane < kStages) mbar_arrive_cluster(leader_empty + 8 * lane + dep);
                if (j == 2) {
                    named_bar_arrive((wg == 0 ? 6 : 5) + dep, 384);
                    named_bar_arrive(wg == 2 ? 6 : 7, 384);
                }
                mbar_wait(sb + kXBarOff + 8 * j, 0);
                my_turn();
                asm volatile("wgmma.fence.sync.aligned;" ::: "memory");
#pragma unroll
                for (int k = 0; k < 8; k++) wgmma_rs(acc0, a[8 * j + k], desc + (j * kXSlabBytes >> 4) + desc_k(k), j + k != 0);
                pass_turn();
            }
            asm volatile("wgmma.commit_group.sync.aligned;" ::: "memory");
            named_bar_sync(5 + wg, 384);
            asm volatile("wgmma.wait_group.sync.aligned 0;" ::: "memory");
            release_stage();
            release_stage();
            uint32_t p[8];
            pack(p, acc0);
            put(p, static_tile(0));
            pack(p, acc0 + 16);
            put(p, static_tile(1));
        }

        float acc[16];
        uint32_t park[kPark][8], park_last;
        int parked = 0;
        asm volatile("mov.b32 %0, %0;" : "+r"(st_off));
        auto spill_addr = [&](int base, int shift, int zero) {
            return ((st_off + zero) >> shift) + (sb - (sb >> shift) + kSpillOff + base - (kOutOff >> shift));
        };
        asm volatile("mov.b32 %0, 0;" : "=r"(park_last));
#pragma unroll
        for (int k = 0; k < kPark * 8; k++) asm volatile("mov.b32 %0, 0;" : "=r"(park[k / 8][k % 8]));
#pragma unroll 1
        while (true) {
            mbar_wait(sb + kFullOff + 8 * s, ph);
            const int t = lds32(sb + kSlotOff + 4 * s);
            if (t >= num_tiles) break;
            const uint64_t desc = make_desc(sb + s * kStageBytes, 6144);
            my_turn();
            asm volatile("wgmma.fence.sync.aligned;" ::: "memory");
#pragma unroll
            for (int k = 0; k < 24; k++) {
                if (k == 20) pass_turn();
                wgmma_rs(acc, a[k], desc + desc_k(k), k != 0);
            }
            asm volatile("wgmma.commit_group.sync.aligned;" ::: "memory");
            asm volatile("wgmma.wait_group.sync.aligned 0;" ::: "memory");
            release_stage();
            const int keep = t >= kn.park_from ? kPark + 1 : t >= kn.mid_from && t < kn.mid_to ? kn.mid_n : 0;
            if (parked < keep) {
#pragma unroll
                for (int k = 0; k < kPark; k++)
                    if (parked == k) pack(park[k], acc);
                if (parked == kPark) {
                    uint32_t p[8];
                    pack(p, acc);
                    asm volatile("st.shared.v4.b32 [%0], {%1, %2, %3, %4};"
                                 ::"r"(spill_addr(0, 0, 0)), "r"(p[0]), "r"(p[1]), "r"(p[2]), "r"(p[3]) : "memory");
                    asm volatile("st.shared.v2.b32 [%0], {%1, %2};" ::"r"(spill_addr(6144, 1, t >> 24)), "r"(p[4]), "r"(p[5]) : "memory");
                    sts32(spill_addr(9216, 2, t >> 24), p[6]);
                    asm volatile("xor.b32 %0, %1, %2;" : "=r"(park_last) : "r"(p[7]), "r"(st_off));
                }
                if (threadIdx.x == 0) sts32(sb + kPSlotOff + 4 * parked, t);
                parked++;
            } else {
                uint32_t p[8];
                pack(p, acc);
                put(p, t);
                if (parked > keep) {
#pragma unroll
                    for (int k = 2; k >= 0; k--)
                        if (k < parked) put(park[k], threadIdx.x == 0 ? lds32(sb + kPSlotOff + 4 * k) : 0);
                    parked = 0;
                }
            }
        }
#pragma unroll
        for (int k = 0; k < kPark; k++)
            if (k < parked) put(park[k], threadIdx.x == 0 ? lds32(sb + kPSlotOff + 4 * k) : 0);
        if (parked > kPark) {
            uint32_t p[8];
            asm volatile("ld.shared.v4.b32 {%0, %1, %2, %3}, [%4];"
                         : "=r"(p[0]), "=r"(p[1]), "=r"(p[2]), "=r"(p[3]) : "r"(spill_addr(0, 0, 0)) : "memory");
            asm volatile("ld.shared.v2.b32 {%0, %1}, [%2];" : "=r"(p[4]), "=r"(p[5]) : "r"(spill_addr(6144, 1, parked >> 24)) : "memory");
            p[6] = lds32(spill_addr(9216, 2, parked >> 24));
            asm volatile("xor.b32 %0, %1, %2;" : "=r"(p[7]) : "r"(park_last), "r"(st_off));
            put(p, threadIdx.x == 0 ? lds32(sb + kPSlotOff + 4 * kPark) : 0);
        }
#pragma unroll 1
        for (int k = 0; k < 2; k++) {
            mbar_wait(sb + kOEmptyOff + 8 * ob, oph);
            if (threadIdx.x == 0) sts32(sb + kOSlotOff + 4 * ob, num_tiles);
            if (lane == 0) mbar_arrive(sb + kOFullOff + 8 * ob);
            if (++ob == kOutBufs) { ob = 0; oph ^= 1; }
        }
    } else {
        asm volatile("setmaxnreg.dec.sync.aligned.u32 32;");
        const int role = (threadIdx.x >> 5) & 3;
        const bool lead = (threadIdx.x & 31) == 0;
        if (role >= 2) {
            const int par = role & 1;
            if (lead) {
                if (par == 0) {
#pragma unroll
                    for (int b = 0; b < kOutBufs; b++) {
                        mbar_init(sb + kOFullOff + 8 * b, 12);
                        mbar_init(sb + kOEmptyOff + 8 * b, 1);
                    }
                } else {
#pragma unroll
                    for (int s = 0; s < kStages; s++) {
                        mbar_init(sb + kFullOff + 8 * s, 1);
                        mbar_init(sb + kEmptyOff + 8 * s, 24);
                        if (s < 2) mbar_arrive(sb + kFullOff + 8 * s);
                    }
                    prefetch_map(&tm_x);
                    prefetch_map(&tm_o);
                }
                asm volatile("fence.mbarrier_init.release.cluster;" ::: "memory");
            }
            cluster_arrive();
            cluster_wait();
            if (lead) {
                uint64_t policy;
                asm volatile("createpolicy.fractional.L2::evict_normal.b64 %0, 1.0;" : "=l"(policy));
                int head = par, tail = par, freed = par, held = 0, busy = 0, pos = 0;
                uint32_t ph = 0;
#pragma unroll 1
                while (true) {
                    mbar_wait(sb + kOFullOff + 8 * head, ph);
                    const int t = lds32(sb + kOSlotOff + 4 * head);
                    int hold = 0, lag = 0;
                    if (t < num_tiles) {
                        held++;
                        pos = max(pos, t);
                        if ((head += 2) >= kOutBufs) { head = par; ph ^= 1; }
#pragma unroll
                        for (int k = 0; k < 6; k++)
                            if (pos >= kn.hold_pos[k]) hold = kn.hold[k];
                        if (pos >= kn.park_from) lag = min(kn.lag, 3 - hold);
                        if (pos >= kn.stream_from) asm volatile("createpolicy.fractional.L2::evict_first.b64 %0, 1.0;" : "=l"(policy));
                    }
#pragma unroll 1
                    for (; held > hold; held--, busy++) {
                        asm volatile("cp.async.bulk.tensor.3d.global.shared::cta.bulk_group.L2::cache_hint [%0, {%2, %3, %4}], [%1], %5;"
                                     ::"l"(&tm_o), "r"(sb + kOutOff + tail * kOutBytes), "r"(0), "r"((int)rank * 3),
                                       "r"(lds32(sb + kOSlotOff + 4 * tail) * kTilePx), "l"(policy) : "memory");
                        asm volatile("cp.async.bulk.commit_group;" ::: "memory");
                        if ((tail += 2) >= kOutBufs) tail = par;
                    }
#pragma unroll 1
                    while (busy > lag) {
                        busy--;
                        if (busy == 0) asm volatile("cp.async.bulk.wait_group.read 0;" ::: "memory");
                        else if (busy == 1) asm volatile("cp.async.bulk.wait_group.read 1;" ::: "memory");
                        else if (busy == 2) asm volatile("cp.async.bulk.wait_group.read 2;" ::: "memory");
                        else asm volatile("cp.async.bulk.wait_group.read 3;" ::: "memory");
                        mbar_arrive(sb + kOEmptyOff + 8 * freed);
                        if ((freed += 2) >= kOutBufs) freed = par;
                    }
                    if (t >= num_tiles) break;
                }
            }
        } else if (role == 1) {
            const uint32_t t_start = __shfl_sync(0xffffffffu, globaltimer(), 0);
            const uint32_t my_slot = sb + kSlotOff + 4 * min(threadIdx.x & 31, kStages - 1);
            sts32(my_slot, 0);
            __threadfence_block();
            cluster_arrive();
#pragma unroll 1
            for (int t = blockIdx.x + gridDim.x; t < num_tiles; t += gridDim.x) {
                const uint32_t due = kn.pf_t0 + (t - gridDim.x) * kn.pf_dt / gridDim.x;
                for (int n = 0; globaltimer() - t_start < due && n < 4096; n++) __nanosleep(50);
                int p0 = 0, l0 = kn.lead[0], slope = 0;
#pragma unroll
                for (int k = 0; k < 8; k++)
                    if (t >= kn.lead_pos[k]) { p0 = kn.lead_pos[k]; l0 = kn.lead[k]; slope = kn.lead_slope[k]; }
                const int max_lead = l0 + ((t - p0) * slope >> 16);
                for (int n = 0; t > max_lead && n < 4096; n++) {
                    const int front = __reduce_max_sync(0xffffffffu, lds32_volatile(my_slot));
                    if (t - max_lead <= front || front >= num_tiles) break;
                    __nanosleep(50);
                }
                const char* src = (const char*)x + (size_t)t * kStageBytes;
                if (t < kn.pull_to) {
#pragma unroll
                    for (int j = 0; j < 6; j++)
                        asm volatile("cp.async.ca.shared.global.L2::128B [%0], [%1], 4;"
                                     ::"r"(sb + kScratchOff + (threadIdx.x & 31) * 4 + j * (num_tiles >> 24)),
                                       "l"(src + (j * 32 + (threadIdx.x & 31)) * 128) : "memory");
                } else if (lead) {
                    asm volatile("cp.async.bulk.prefetch.L2.global [%0], %1;" ::"l"(src), "r"(kStageBytes) : "memory");
                }
            }
            asm volatile("cp.async.wait_all;" ::: "memory");
            cluster_wait();
        } else {
            cluster_arrive();
            cluster_wait();
            if (lead && rank == 0) {
                const uint32_t peer = map_to_cta(sb, 1);
                const int nstatic = kn.static_tiles * (gridDim.x >> 1);
                const unsigned last_fetch = num_tiles - nstatic + gridDim.x - 1;
                mbar_wait(sb + kEmptyOff, 0);
                mbar_wait(sb + kEmptyOff + 8, 0);
                int s = 2, i = 2;
                uint32_t ph = 0;
                auto step = [&](unsigned& raw) -> bool {
                    const int t = nstatic + raw;
                    const bool valid = t < num_tiles;
                    raw = static_tile(i + 2) - nstatic;
                    if (i + 2 >= kn.static_tiles && valid)
                        asm volatile("atom.global.inc.u32 %0, [%1], %2;" : "+r"(raw) : "l"(&g_tile_counter), "r"(last_fetch) : "memory");
                    mbar_wait(sb + kEmptyOff + 8 * s, ph);
                    const uint32_t full = kFullOff + 8 * s, slot = kSlotOff + 4 * s;
                    const uint32_t bytes = valid ? kStageBytes : 0;
                    sts32(sb + slot, t);
                    mbar_expect_tx(sb + full, bytes);
                    asm volatile("mbarrier.arrive.expect_tx.shared::cluster.b64 _, [%0], %1;" ::"r"(peer + full), "r"(bytes + 4) : "memory");
                    asm volatile("st.async.weak.shared::cluster.mbarrier::complete_tx::bytes.b32 [%0], %1, [%2];"
                                 ::"r"(peer + slot), "r"(t), "r"(peer + full) : "memory");
                    if (!valid) return false;
                    asm volatile(
                        "cp.async.bulk.tensor.4d.shared::cluster.global.mbarrier::complete_tx::bytes.multicast::cluster "
                        "[%0], [%1, {%3, %3, %3, %4}], [%2], %5;"
                        ::"r"(sb + s * kStageBytes), "l"(&tm_x), "r"(sb + full), "r"(0), "r"(t * (kTilePx / 8)),
                          "h"((uint16_t)3) : "memory");
                    if (++s == kStages) { s = 0; ph ^= 1; }
                    i++;
                    return true;
                };
                unsigned raw0 = static_tile(2) - nstatic, raw1 = static_tile(3) - nstatic;
#pragma unroll 1
                while (step(raw0) && step(raw1)) {}
#pragma unroll 1
                for (int k = 1; k < kStages; k++) {
                    if (++s == kStages) { s = 0; ph ^= 1; }
                    mbar_wait(sb + kEmptyOff + 8 * s, ph);
                }
            }
        }
    }
}

typedef CUresult (*EncodeTiledFn)(CUtensorMap*, CUtensorMapDataType, cuuint32_t, void*, const cuuint64_t*,
                                  const cuuint64_t*, const cuuint32_t*, const cuuint32_t*, CUtensorMapInterleave,
                                  CUtensorMapSwizzle, CUtensorMapL2promotion, CUtensorMapFloatOOBfill);

}

extern "C" void kernel_launch(void* const* d_in, const int* in_sizes, int n_in, void* d_out, int out_size) {
    (void)n_in; (void)out_size;
    const __nv_bfloat16* x = (const __nv_bfloat16*)d_in[0];
    const __nv_bfloat16* dw = (const __nv_bfloat16*)d_in[1];
    const __nv_bfloat16* pw = (const __nv_bfloat16*)d_in[2];
    const int pixels = in_sizes[0] / kC;

    static EncodeTiledFn encode = nullptr;
    static int grid = 0;
    if (!encode) {
        void* fn = nullptr;
        cudaDriverEntryPointQueryResult qr;
        cudaGetDriverEntryPoint("cuTensorMapEncodeTiled", &fn, cudaEnableDefault, &qr);
        encode = (EncodeTiledFn)fn;
        cudaFuncSetAttribute(dwsep_kernel, cudaFuncAttributeMaxDynamicSharedMemorySize, kSmemBytes);
        int sms = 0, clusters = 0;
        cudaDeviceGetAttribute(&sms, cudaDevAttrMultiProcessorCount, 0);
        cudaLaunchConfig_t cfg = {};
        cudaLaunchAttribute attr = {};
        attr.id = cudaLaunchAttributeClusterDimension;
        attr.val.clusterDim.x = 2;
        attr.val.clusterDim.y = attr.val.clusterDim.z = 1;
        cfg.gridDim = dim3(sms & ~1);
        cfg.blockDim = dim3(kThreads);
        cfg.dynamicSmemBytes = kSmemBytes;
        cfg.attrs = &attr;
        cfg.numAttrs = 1;
        if (cudaOccupancyMaxActiveClusters(&clusters, dwsep_kernel, &cfg) != cudaSuccess || clusters < 1) {
            (void)cudaGetLastError();
            clusters = sms / 2;
        }
        grid = 2 * (clusters < sms / 2 ? clusters : sms / 2);
    }

    CUtensorMap tm_w, tm_x0, tm_x, tm_o;
    auto make_map = [&](CUtensorMap* m, const void* base, int rank, const cuuint64_t* dims, const cuuint64_t* strides,
                        const cuuint32_t* box, CUtensorMapL2promotion promo) {
        const cuuint32_t ones[4] = {1, 1, 1, 1};
        encode(m, CU_TENSOR_MAP_DATA_TYPE_BFLOAT16, rank, (void*)base, dims, strides, box, ones,
               CU_TENSOR_MAP_INTERLEAVE_NONE, CU_TENSOR_MAP_SWIZZLE_128B, promo, CU_TENSOR_MAP_FLOAT_OOB_FILL_NONE);
    };
    {
        const cuuint64_t dims[3] = {64, kC, 6}, strides[2] = {kC * 2, 128};
        const cuuint32_t box[3] = {64, 64, 3};
        make_map(&tm_w, pw, 3, dims, strides, box, CU_TENSOR_MAP_L2_PROMOTION_L2_128B);
    }
    {
        const cuuint64_t dims[4] = {64, 8, 6, (cuuint64_t)pixels / 8}, strides[3] = {kC * 2, 128, kC * 2 * 8};
        const cuuint32_t box0[4] = {64, 8, 2, 8}, box[4] = {64, 8, 6, kTilePx / 8};
        make_map(&tm_x0, x, 4, dims, strides, box0, CU_TENSOR_MAP_L2_PROMOTION_L2_128B);
        make_map(&tm_x, x, 4, dims, strides, box, CU_TENSOR_MAP_L2_PROMOTION_L2_128B);
    }
    {
        const cuuint64_t dims[3] = {64, 6, (cuuint64_t)pixels}, strides[2] = {128, kC * 2};
        const cuuint32_t box[3] = {64, 3, kTilePx};
        make_map(&tm_o, d_out, 3, dims, strides, box, CU_TENSOR_MAP_L2_PROMOTION_NONE);
    }
    Knobs kn = g_knobs;
    for (int k = 0; k < 8; k++)
        kn.lead_slope[k] = k < 7 ? (kn.lead[k + 1] - kn.lead[k]) * 65536 / (kn.lead_pos[k + 1] - kn.lead_pos[k]) : 0;
    dwsep_kernel<<<grid, kThreads, kSmemBytes, cudaStreamPerThread>>>(tm_w, tm_x0, tm_x, tm_o, x, dw, pw,
                                                                      pixels / kTilePx, kn);
}
```

```cpp
#include <cuda_runtime.h>
#include <cuda_bf16.h>
#include <cuda.h>
#include <stdint.h>

namespace {

constexpr int kC = 384;
constexpr int kTilePx = 32;
constexpr int kStages = 5;
constexpr int kOutBufs = 8;
constexpr int kPark = 5;
constexpr int kThreads = 512;
constexpr int kStageBytes = kTilePx * kC * 2;
constexpr int kOutBytes = kTilePx * 192 * 2;
constexpr int kWChunkBytes = 64 * 192 * 2;
constexpr int kXSlabBytes = 64 * 128 * 2;
constexpr int kWOff = 3 * kStageBytes;
constexpr int kOutOff = kStages * kStageBytes;
constexpr int kSpillOff = kOutOff + kOutBufs * kOutBytes;
constexpr int kDwOff = kSpillOff;
constexpr int kScratchOff = kSpillOff + 1024;
constexpr int kFullOff = kSpillOff + 384 * 28;
constexpr int kEmptyOff = kFullOff + 8 * kStages;
constexpr int kOFullOff = kEmptyOff + 8 * kStages;
constexpr int kOEmptyOff = kOFullOff + 8 * kOutBufs;
constexpr int kWBarOff = kOEmptyOff + 8 * kOutBufs;
constexpr int kXBarOff = kWBarOff + 8 * 3;
constexpr int kDwBarOff = kXBarOff + 8 * 3;
constexpr int kPullBarOff = kDwBarOff + 8;
constexpr int kSlotOff = kPullBarOff + 8;
constexpr int kOSlotOff = kSlotOff + 4 * kStages;
constexpr int kPSlotOff = kOSlotOff + 4 * kOutBufs;
constexpr int kSmemBytes = kPSlotOff + 4 * (kPark + 1);
static_assert(kWChunkBytes == kStageBytes && kWOff + 6 * kWChunkBytes <= kDwOff, "weight staging");
static_assert(kSmemBytes <= 232448, "shared memory");

constexpr int kHoldPts = 8, kLeadPts = 10;
struct Knobs {
    int first_gap;
    int pull_n, pull_t0, pull_dt;
    int pf_from, pf_t0, pf_dt;
    int static_tiles;
    int mid_from, mid_to, mid_n;
    int park_from;
    int stream_from;
    int hold_pos[kHoldPts], hold[kHoldPts];
    int lead_pos[kLeadPts], lead[kLeadPts];
    int lead_slope[kLeadPts];
};
#define DEFAULT_KNOBS {472, 5, 90, 520, 561, 60, 730, 18, 1601, 3150, 2, 3416, 4395, \
    {0, 451, 721, 1081, 2000, 3000, 4267, 4608}, {0, 1, 2, 3, 3, 3, 1, 1}, \
    {0, 819, 1484, 1900, 2224, 2310, 3470, 3750, 4200, 4490}, {345, 365, 544, 380, 355, 360, 88, 155, 180, 170}}
constexpr Knobs g_knobs = DEFAULT_KNOBS;

__device__ unsigned int g_tile_counter;

__device__ __forceinline__ uint32_t smem_u32(const void* p) { return (uint32_t)__cvta_generic_to_shared(p); }

__device__ __forceinline__ void mbar_init(uint32_t bar, uint32_t cnt) {
    asm volatile("mbarrier.init.shared::cta.b64 [%0], %1;" ::"r"(bar), "r"(cnt) : "memory");
}
__device__ __forceinline__ void mbar_expect_tx(uint32_t bar, uint32_t bytes) {
    asm volatile("mbarrier.arrive.expect_tx.shared::cta.b64 _, [%0], %1;" ::"r"(bar), "r"(bytes) : "memory");
}
__device__ __forceinline__ void mbar_arrive(uint32_t bar) {
    asm volatile("mbarrier.arrive.shared::cta.b64 _, [%0];" ::"r"(bar) : "memory");
}
__device__ __forceinline__ void mbar_arrive_cluster(uint32_t bar) {
    asm volatile("mbarrier.arrive.shared::cluster.b64 _, [%0];" ::"r"(bar) : "memory");
}
__device__ __forceinline__ void mbar_wait(uint32_t bar, uint32_t parity) {
    asm volatile(
        "{\n.reg .pred p;\n.reg .u32 n;\n"
        "mbarrier.try_wait.parity.shared::cta.b64 p, [%0], %1;\n"
        "@p bra DONE;\n"
        "mov.u32 n, 0;\n"
        "LOOP:\n"
        "mbarrier.try_wait.parity.shared::cta.b64 p, [%0], %1;\n"
        "@p bra DONE;\n"
        "add.u32 n, n, 1;\n"
        "setp.lt.u32 p, n, 4194304;\n"
        "@p bra LOOP;\n"
        "trap;\n"
        "DONE:\n}" ::"r"(bar), "r"(parity) : "memory");
}
__device__ __forceinline__ uint32_t map_to_cta(uint32_t addr, uint32_t cta) {
    uint32_t r;
    asm("mapa.shared::cluster.u32 %0, %1, %2;" : "=r"(r) : "r"(addr), "r"(cta));
    return r;
}
__device__ __forceinline__ void named_bar_sync(int id, int n) { asm volatile("bar.sync %0, %1;" ::"r"(id), "r"(n) : "memory"); }
__device__ __forceinline__ void named_bar_arrive(int id, int n) { asm volatile("bar.arrive %0, %1;" ::"r"(id), "r"(n) : "memory"); }
__device__ __forceinline__ void cluster_arrive() {
    __syncwarp();
    asm volatile("barrier.cluster.arrive.relaxed.aligned;" ::: "memory");
}
__device__ __forceinline__ void cluster_wait() {
    __syncwarp();
    asm volatile("barrier.cluster.wait.acquire.aligned;" ::: "memory");
}
__device__ __forceinline__ void prefetch_line(const void* p) { asm volatile("prefetch.global.L2 [%0];" ::"l"(p) : "memory"); }
__device__ __forceinline__ void prefetch_map(const CUtensorMap* m) { asm volatile("prefetch.tensormap [%0];" ::"l"(m) : "memory"); }
__device__ __forceinline__ uint32_t globaltimer() {
    uint32_t t;
    asm volatile("mov.u32 %0, %%globaltimer_lo;" : "=r"(t));
    return t;
}
__device__ __forceinline__ uint32_t clock32() {
    uint32_t t;
    asm volatile("mov.u32 %0, %%clock;" : "=r"(t));
    return t;
}
__device__ __forceinline__ int lds32(uint32_t addr) {
    int v;
    asm volatile("ld.shared.b32 %0, [%1];" : "=r"(v) : "r"(addr) : "memory");
    return v;
}
__device__ __forceinline__ int lds32_volatile(uint32_t addr) {
    int v;
    asm volatile("ld.volatile.shared.b32 %0, [%1];" : "=r"(v) : "r"(addr) : "memory");
    return v;
}
__device__ __forceinline__ void sts32(uint32_t addr, int v) { asm volatile("st.shared.b32 [%0], %1;" ::"r"(addr), "r"(v) : "memory"); }

#define ACC4(o) "+f"(d[o]), "+f"(d[o + 1]), "+f"(d[o + 2]), "+f"(d[o + 3])
#define ACC16(o) ACC4(o), ACC4(o + 4), ACC4(o + 8), ACC4(o + 12)
__device__ __forceinline__ void wgmma_rs(float (&d)[32], const uint32_t (&a)[4], uint64_t desc_b, int scale_d) {
    asm volatile(
        "{\n.reg .pred p;\nsetp.ne.b32 p, %37, 0;\n"
        "wgmma.mma_async.sync.aligned.m64n64k16.f32.bf16.bf16 "
        "{%0, %1, %2, %3, %4, %5, %6, %7, %8, %9, %10, %11, %12, %13, %14, %15, "
        "%16, %17, %18, %19, %20, %21, %22, %23, %24, %25, %26, %27, %28, %29, %30, %31}, "
        "{%32, %33, %34, %35}, %36, p, 1, 1, 0;\n}"
        : ACC16(0), ACC16(16)
        : "r"(a[0]), "r"(a[1]), "r"(a[2]), "r"(a[3]), "l"(desc_b), "r"(scale_d));
}
__device__ __forceinline__ void wgmma_rs(float (&d)[16], const uint32_t (&a)[4], uint64_t desc_b, int scale_d) {
    asm volatile(
        "{\n.reg .pred p;\nsetp.ne.b32 p, %21, 0;\n"
        "wgmma.mma_async.sync.aligned.m64n32k16.f32.bf16.bf16 "
        "{%0, %1, %2, %3, %4, %5, %6, %7, %8, %9, %10, %11, %12, %13, %14, %15}, "
        "{%16, %17, %18, %19}, %20, p, 1, 1, 0;\n}"
        : ACC16(0)
        : "r"(a[0]), "r"(a[1]), "r"(a[2]), "r"(a[3]), "l"(desc_b), "r"(scale_d));
}
__device__ __forceinline__ uint64_t make_desc(uint32_t addr, uint32_t group_stride) {
    return (uint64_t(1) << 62) | (uint64_t(group_stride >> 4) << 32) | (uint64_t(1) << 16) | (uint64_t)((addr & 0x3FFFF) >> 4);
}
__device__ __forceinline__ constexpr uint64_t desc_k(int k) { return (uint64_t)(((k >> 2) * 1024 + (k & 3) * 32) >> 4); }

__device__ __forceinline__ uint32_t pack_bf16(float lo, float hi) {
    uint32_t r;
    asm("cvt.rn.bf16x2.f32 %0, %1, %2;" : "=r"(r) : "f"(hi), "f"(lo));
    return r;
}
__device__ __forceinline__ uint32_t mul_bf16x2(uint32_t a, uint32_t b) {
    uint32_t r;
    asm("mul.rn.bf16x2 %0, %1, %2;" : "=r"(r) : "r"(a), "r"(b));
    return r;
}

__global__ void __cluster_dims__(2, 1, 1) __launch_bounds__(kThreads, 1)
dwsep_kernel(const __grid_constant__ CUtensorMap tm_w, const __grid_constant__ CUtensorMap tm_x0,
             const __grid_constant__ CUtensorMap tm_x, const __grid_constant__ CUtensorMap tm_o,
             const __grid_constant__ CUtensorMap tm_pull,
             const __nv_bfloat16* __restrict__ x, const __nv_bfloat16* __restrict__ dw,
             const __nv_bfloat16* __restrict__ pw, int num_tiles, const __grid_constant__ Knobs kn) {
    extern __shared__ __align__(1024) uint8_t smem_raw[];
    const uint32_t sb = smem_u32(smem_raw);

    uint32_t rank;
    asm("mov.u32 %0, %%cluster_ctarank;" : "=r"(rank));
    const int cluster = blockIdx.x >> 1;
    auto static_tile = [&](int i) { return (i >> 1) * gridDim.x + cluster * 2 + (i & 1); };

    if (threadIdx.x < 32) {
        prefetch_line(threadIdx.x < 18 ? (const char*)pw + (blockIdx.x & 127) * 2304 + threadIdx.x * 128
                                       : (const char*)dw + min(threadIdx.x - 18, 5) * 128);
    } else if (threadIdx.x < 224) {
        const uint32_t c0 = __shfl_sync(0xffffffffu, clock32(), 0), chunk = (threadIdx.x >> 5) - 1;
        const uint32_t delay = ((chunk >> 1) * gridDim.x + blockIdx.x) * kn.first_gap >> 7;
        for (int n = 0; clock32() - c0 < delay && n < 1024; n++) {}
        prefetch_line((const char*)x + (size_t)blockIdx.x * kStageBytes + (threadIdx.x & 31) * 768 + chunk * 128);
    } else if (threadIdx.x == 288) {
        prefetch_map(&tm_w);
        prefetch_map(&tm_x0);
        if (rank == 1) prefetch_map(&tm_pull);
    }
    if (threadIdx.x >> 5 == 8) {
        if (threadIdx.x == 256) {
#pragma unroll
            for (int b = 0; b < 7; b++) mbar_init(sb + kWBarOff + 8 * b, 1);
            asm volatile("fence.proxy.async.shared::cta;" ::: "memory");
        }
        __syncwarp();
        named_bar_arrive(8, 384);
        if (threadIdx.x == 256) {
            mbar_expect_tx(sb + kDwBarOff, kC * 2);
            asm volatile("cp.async.bulk.shared::cluster.global.mbarrier::complete_tx::bytes [%0], [%1], %2, [%3];"
                         ::"r"(sb + kDwOff), "l"(dw), "r"(kC * 2), "r"(sb + kDwBarOff) : "memory");
#pragma unroll
            for (int j = 0; j < 3; j++) {
                mbar_expect_tx(sb + kWBarOff + 8 * j, 2 * kWChunkBytes);
#pragma unroll
                for (int c = 2 * j; c < 2 * j + 2; c++)
                    asm volatile("cp.async.bulk.tensor.3d.shared::cluster.global.mbarrier::complete_tx::bytes [%0], [%1, {%3, %4, %5}], [%2];"
                                 ::"r"(sb + kWOff + c * kWChunkBytes), "l"(&tm_w), "r"(sb + kWBarOff + 8 * j), "r"(0), "r"(c * 64),
                                   "r"((int)rank * 3) : "memory");
                mbar_expect_tx(sb + kXBarOff + 8 * j, kXSlabBytes);
                asm volatile("cp.async.bulk.tensor.4d.shared::cluster.global.mbarrier::complete_tx::bytes [%0], [%1, {%3, %3, %4, %5}], [%2];"
                             ::"r"(sb + j * kXSlabBytes), "l"(&tm_x0), "r"(sb + kXBarOff + 8 * j), "r"(0), "r"(2 * j),
                               "r"(cluster * 8) : "memory");
            }
        }
        __syncwarp();
    }

    if (threadIdx.x < 384) {
        asm volatile("setmaxnreg.inc.sync.aligned.u32 160;");
        cluster_arrive();
        if (threadIdx.x >> 5 != 8) named_bar_sync(8, 384);
        const int wg = __shfl_sync(0xffffffffu, threadIdx.x >> 7, 0);
        const int warp = (threadIdx.x >> 5) & 3;
        const int lane = threadIdx.x & 31;
        const int mi = lane >> 3, ri = lane & 7;
        const uint32_t leader_empty = map_to_cta(sb + kEmptyOff, 0);
        uint32_t st_off = sb + kOutOff + (((mi >> 1) * 8 + ri) * 3 + wg) * 128 + (((2 * warp + (mi & 1)) ^ ((3 * ri + wg) & 7)) << 4);
        int s = 0, ob = 0;
        uint32_t ph = 0, oph = 1;
        auto release_stage = [&]() {
            if (lane == 0) mbar_arrive_cluster(leader_empty + 8 * s);
            if (++s == kStages) { s = 0; ph ^= 1; }
        };
        auto pack = [&](uint32_t (&p)[8], const float* acc) {
#pragma unroll
            for (int k = 0; k < 8; k++) p[k] = pack_bf16(acc[2 * k], acc[2 * k + 1]);
        };
        auto put = [&](const uint32_t (&p)[8], int t) {
            mbar_wait(sb + kOEmptyOff + 8 * ob, oph);
            if (threadIdx.x == 0) sts32(sb + kOSlotOff + 4 * ob, t);
#pragma unroll
            for (int q = 0; q < 2; q++)
                asm volatile("stmatrix.sync.aligned.m8n8.x4.trans.shared.b16 [%0], {%1, %2, %3, %4};"
                             ::"r"(st_off + ob * kOutBytes + q * (16 * 384)), "r"(p[4 * q]), "r"(p[4 * q + 1]),
                               "r"(p[4 * q + 2]), "r"(p[4 * q + 3]) : "memory");
            asm volatile("fence.proxy.async.shared::cta;" ::: "memory");
            __syncwarp();
            if (lane == 0) mbar_arrive(sb + kOFullOff + 8 * ob);
            if (++ob == kOutBufs) { ob = 0; oph ^= 1; }
        };
        auto my_turn = [&]() { named_bar_sync(2 + wg, 256); };
        auto pass_turn = [&]() { named_bar_arrive(wg == 2 ? 2 : 3 + wg, 256); };
        if (wg == 2) pass_turn();

        uint32_t a[24][4];
        {
            float acc0[32];
            uint32_t dws[48];
            mbar_wait(sb + kDwBarOff, 0);
#pragma unroll
            for (int k = 0; k < 48; k++) dws[k] = lds32(sb + kDwOff + k * 16 + (lane & 3) * 4);
            cluster_wait();
            if (lane < 3) mbar_arrive_cluster(leader_empty + 8 * lane);
            const uint32_t wbase = sb + kWOff + wg * 8192 + ((mi >> 1) * 8 + ri) * 128 + (((2 * warp + (mi & 1)) ^ ri) << 4);
            const uint64_t desc = make_desc(sb, 2048);
#pragma unroll
            for (int j = 0; j < 3; j++) {
                mbar_wait(sb + kWBarOff + 8 * j, 0);
#pragma unroll
                for (int k = 8 * j; k < 8 * j + 8; k++) {
                    asm volatile("ldmatrix.sync.aligned.m8n8.x4.trans.shared.b16 {%0, %1, %2, %3}, [%4];"
                                 : "=r"(a[k][0]), "=r"(a[k][1]), "=r"(a[k][2]), "=r"(a[k][3])
                                 : "r"(wbase + (k >> 2) * kWChunkBytes + (k & 3) * 2048) : "memory");
                    a[k][0] = mul_bf16x2(a[k][0], dws[2 * k]);
                    a[k][1] = mul_bf16x2(a[k][1], dws[2 * k]);
                    a[k][2] = mul_bf16x2(a[k][2], dws[2 * k + 1]);
                    a[k][3] = mul_bf16x2(a[k][3], dws[2 * k + 1]);
                }
                uint32_t dep = 0;
#pragma unroll
                for (int k = 8 * j; k < 8 * j + 8; k++) dep ^= a[k][3];
                dep &= num_tiles >> 24;
                if (j == 0 && lane >= 3 && lane < kStages) mbar_arrive_cluster(leader_empty + 8 * lane + dep);
                if (j == 2) {
                    named_bar_arrive((wg == 0 ? 6 : 5) + dep, 384);
                    named_bar_arrive(wg == 2 ? 6 : 7, 384);
                }
                mbar_wait(sb + kXBarOff + 8 * j, 0);
                my_turn();
                asm volatile("wgmma.fence.sync.aligned;" ::: "memory");
#pragma unroll
                for (int k = 0; k < 8; k++) wgmma_rs(acc0, a[8 * j + k], desc + (j * kXSlabBytes >> 4) + desc_k(k), j + k != 0);
                pass_turn();
            }
            asm volatile("wgmma.commit_group.sync.aligned;" ::: "memory");
            named_bar_sync(5 + wg, 384);
            asm volatile("wgmma.wait_group.sync.aligned 0;" ::: "memory");
            release_stage();
            release_stage();
            uint32_t p[8];
            pack(p, acc0);
            put(p, static_tile(0));
            pack(p, acc0 + 16);
            put(p, static_tile(1));
        }

        float acc[16];
        uint32_t park[kPark][8], park_last;
        int parked = 0;
        asm volatile("mov.b32 %0, %0;" : "+r"(st_off));
        auto spill_addr = [&](int base, int shift, int zero) {
            return ((st_off + zero) >> shift) + (sb - (sb >> shift) + kSpillOff + base - (kOutOff >> shift));
        };
        asm volatile("mov.b32 %0, 0;" : "=r"(park_last));
#pragma unroll
        for (int k = 0; k < kPark * 8; k++) asm volatile("mov.b32 %0, 0;" : "=r"(park[k / 8][k % 8]));
#pragma unroll 1
        while (true) {
            mbar_wait(sb + kFullOff + 8 * s, ph);
            const int t = lds32(sb + kSlotOff + 4 * s);
            if (t >= num_tiles) break;
            const uint64_t desc = make_desc(sb + s * kStageBytes, 6144);
            my_turn();
            asm volatile("wgmma.fence.sync.aligned;" ::: "memory");
#pragma unroll
            for (int k = 0; k < 24; k++) {
                if (k == 20) pass_turn();
                wgmma_rs(acc, a[k], desc + desc_k(k), k != 0);
            }
            asm volatile("wgmma.commit_group.sync.aligned;" ::: "memory");
            asm volatile("wgmma.wait_group.sync.aligned 0;" ::: "memory");
            release_stage();
            const int keep = t >= kn.park_from ? kPark + 1 : t >= kn.mid_from && t < kn.mid_to ? kn.mid_n : 0;
            if (parked < keep) {
#pragma unroll
                for (int k = 0; k < kPark; k++)
                    if (parked == k) pack(park[k], acc);
                if (parked == kPark) {
                    uint32_t p[8];
                    pack(p, acc);
                    mbar_wait(sb + kPullBarOff, 0);
                    asm volatile("st.shared.v4.b32 [%0], {%1, %2, %3, %4};"
                                 ::"r"(spill_addr(0, 0, 0)), "r"(p[0]), "r"(p[1]), "r"(p[2]), "r"(p[3]) : "memory");
                    asm volatile("st.shared.v2.b32 [%0], {%1, %2};" ::"r"(spill_addr(6144, 1, t >> 24)), "r"(p[4]), "r"(p[5]) : "memory");
                    sts32(spill_addr(9216, 2, t >> 24), p[6]);
                    asm volatile("xor.b32 %0, %1, %2;" : "=r"(park_last) : "r"(p[7]), "r"(st_off));
                }
                if (threadIdx.x == 0) sts32(sb + kPSlotOff + 4 * parked, t);
                parked++;
            } else {
                uint32_t p[8];
                pack(p, acc);
                put(p, t);
                if (parked > keep) {
#pragma unroll
                    for (int k = 2; k >= 0; k--)
                        if (k < parked) put(park[k], threadIdx.x == 0 ? lds32(sb + kPSlotOff + 4 * k) : 0);
                    parked = 0;
                }
            }
        }
#pragma unroll
        for (int k = 0; k < kPark; k++)
            if (k < parked) put(park[k], threadIdx.x == 0 ? lds32(sb + kPSlotOff + 4 * k) : 0);
        if (parked > kPark) {
            uint32_t p[8];
            asm volatile("ld.shared.v4.b32 {%0, %1, %2, %3}, [%4];"
                         : "=r"(p[0]), "=r"(p[1]), "=r"(p[2]), "=r"(p[3]) : "r"(spill_addr(0, 0, 0)) : "memory");
            asm volatile("ld.shared.v2.b32 {%0, %1}, [%2];" : "=r"(p[4]), "=r"(p[5]) : "r"(spill_addr(6144, 1, parked >> 24)) : "memory");
            p[6] = lds32(spill_addr(9216, 2, parked >> 24));
            asm volatile("xor.b32 %0, %1, %2;" : "=r"(p[7]) : "r"(park_last), "r"(st_off));
            put(p, threadIdx.x == 0 ? lds32(sb + kPSlotOff + 4 * kPark) : 0);
        }
        mbar_wait(sb + kPullBarOff, 0);
#pragma unroll 1
        for (int k = 0; k < 2; k++) {
            mbar_wait(sb + kOEmptyOff + 8 * ob, oph);
            if (threadIdx.x == 0) sts32(sb + kOSlotOff + 4 * ob, num_tiles);
            if (lane == 0) mbar_arrive(sb + kOFullOff + 8 * ob);
            if (++ob == kOutBufs) { ob = 0; oph ^= 1; }
        }
    } else {
        asm volatile("setmaxnreg.dec.sync.aligned.u32 32;");
        const int role = (threadIdx.x >> 5) & 3;
        const bool lead = (threadIdx.x & 31) == 0;
        if (role >= 2) {
            const int par = role & 1;
            if (lead) {
                if (par == 0) {
#pragma unroll
                    for (int b = 0; b < kOutBufs; b++) {
                        mbar_init(sb + kOFullOff + 8 * b, 12);
                        mbar_init(sb + kOEmptyOff + 8 * b, 1);
                    }
                } else {
#pragma unroll
                    for (int s = 0; s < kStages; s++) {
                        mbar_init(sb + kFullOff + 8 * s, 1);
                        mbar_init(sb + kEmptyOff + 8 * s, 24);
                        if (s < 2) mbar_arrive(sb + kFullOff + 8 * s);
                    }
                    prefetch_map(&tm_x);
                    prefetch_map(&tm_o);
                }
                asm volatile("fence.mbarrier_init.release.cluster;" ::: "memory");
            }
            cluster_arrive();
            cluster_wait();
            if (lead) {
                uint64_t normal, streaming;
                asm volatile("createpolicy.fractional.L2::evict_normal.b64 %0, 1.0;" : "=l"(normal));
                asm volatile("createpolicy.fractional.L2::evict_first.b64 %0, 1.0;" : "=l"(streaming));
                int head = par, tail = par, held = 0, pos = 0, k = 0, hold = 0;
                uint32_t ph = 0;
#pragma unroll 1
                while (true) {
                    mbar_wait(sb + kOFullOff + 8 * head, ph);
                    const int t = lds32(sb + kOSlotOff + 4 * head);
                    if (t < num_tiles) {
                        held++;
                        pos = max(pos, t);
                        if ((head += 2) >= kOutBufs) { head = par; ph ^= 1; }
#pragma unroll 1
                        for (; k < kHoldPts && pos >= kn.hold_pos[k]; k++) hold = kn.hold[k];
                    } else {
                        hold = 0;
                    }
                    int freed = tail, n = 0;
#pragma unroll 1
                    for (; held > hold; held--, n++) {
                        asm volatile("cp.async.bulk.tensor.3d.global.shared::cta.bulk_group.L2::cache_hint [%0, {%2, %3, %4}], [%1], %5;"
                                     ::"l"(&tm_o), "r"(sb + kOutOff + tail * kOutBytes), "r"(0), "r"((int)rank * 3),
                                       "r"(lds32(sb + kOSlotOff + 4 * tail) * kTilePx),
                                       "l"(pos >= kn.stream_from ? streaming : normal) : "memory");
                        asm volatile("cp.async.bulk.commit_group;" ::: "memory");
                        if ((tail += 2) >= kOutBufs) tail = par;
                    }
#pragma unroll 1
                    while (n-- > 0) {
                        if (n == 0) asm volatile("cp.async.bulk.wait_group.read 0;" ::: "memory");
                        else if (n == 1) asm volatile("cp.async.bulk.wait_group.read 1;" ::: "memory");
                        else if (n == 2) asm volatile("cp.async.bulk.wait_group.read 2;" ::: "memory");
                        else asm volatile("cp.async.bulk.wait_group.read 3;" ::: "memory");
                        mbar_arrive(sb + kOEmptyOff + 8 * freed);
                        if ((freed += 2) >= kOutBufs) freed = par;
                    }
                    if (t >= num_tiles) break;
                }
            }
        } else if (role == 1) {
            const uint32_t t_start = __shfl_sync(0xffffffffu, globaltimer(), 0);
            const uint32_t my_slot = sb + kSlotOff + 4 * min(threadIdx.x & 31, kStages - 1);
            sts32(my_slot, 0);
            __threadfence_block();
            cluster_arrive();
            int k = 0;
#pragma unroll 1
            for (int t = blockIdx.x + gridDim.x; t < num_tiles; t += gridDim.x) {
                if (t < kn.pf_from) continue;
                const uint32_t due = kn.pf_t0 + (t - gridDim.x) * kn.pf_dt / gridDim.x;
                for (int n = 0; globaltimer() - t_start < due && n < 4096; n++) __nanosleep(50);
#pragma unroll 1
                while (k + 1 < kLeadPts && t >= kn.lead_pos[k + 1]) k++;
                const int max_lead = kn.lead[k] + ((t - kn.lead_pos[k]) * kn.lead_slope[k] >> 16);
                for (int n = 0; t > max_lead && n < 4096; n++) {
                    const int front = __reduce_max_sync(0xffffffffu, lds32_volatile(my_slot));
                    if (t - max_lead <= front || front >= num_tiles) break;
                    __nanosleep(50);
                }
                if (lead)
                    asm volatile("cp.async.bulk.prefetch.L2.global [%0], %1;"
                                 ::"l"((const char*)x + (size_t)t * kStageBytes), "r"(kStageBytes) : "memory");
            }
            cluster_wait();
        } else {
            const uint32_t t_start = __shfl_sync(0xffffffffu, globaltimer(), 0);
            if (lead) {
                mbar_init(sb + kPullBarOff, 1);
                asm volatile("fence.proxy.async.shared::cta;" ::: "memory");
                mbar_expect_tx(sb + kPullBarOff, rank * 3072 * kn.pull_n);
            }
            __threadfence_block();
            cluster_arrive();
            if (rank == 1 && lead) {
#pragma unroll 1
                for (int i = 0; i < kn.pull_n; i++) {
                    const uint32_t due = kn.pull_t0 + (i * gridDim.x + blockIdx.x) * kn.pull_dt / gridDim.x;
                    for (int n = 0; globaltimer() - t_start < due && n < 4096; n++) {}
                    asm volatile("cp.async.bulk.tensor.2d.shared::cluster.global.mbarrier::complete_tx::bytes [%0], [%1, {%3, %4}], [%2];"
                                 ::"r"(sb + kScratchOff), "l"(&tm_pull), "r"(sb + kPullBarOff), "r"(0), "r"(static_tile(i + 2) * 192) : "memory");
                }
            }
            cluster_wait();
            if (lead && rank == 0) {
                const uint32_t peer = map_to_cta(sb, 1);
                const int nstatic = kn.static_tiles * (gridDim.x >> 1);
                const unsigned last_fetch = num_tiles - nstatic + gridDim.x - 1;
                mbar_wait(sb + kEmptyOff, 0);
                mbar_wait(sb + kEmptyOff + 8, 0);
                int s = 2, i = 2;
                uint32_t ph = 0;
                auto step = [&](unsigned& raw) -> bool {
                    const int t = nstatic + raw;
                    const bool valid = t < num_tiles;
                    raw = static_tile(i + 2) - nstatic;
                    if (i + 2 >= kn.static_tiles && valid)
                        asm volatile("atom.global.inc.u32 %0, [%1], %2;" : "+r"(raw) : "l"(&g_tile_counter), "r"(last_fetch) : "memory");
                    mbar_wait(sb + kEmptyOff + 8 * s, ph);
                    const uint32_t full = kFullOff + 8 * s, slot = kSlotOff + 4 * s;
                    const uint32_t bytes = valid ? kStageBytes : 0;
                    sts32(sb + slot, t);
                    mbar_expect_tx(sb + full, bytes);
                    asm volatile("mbarrier.arrive.expect_tx.shared::cluster.b64 _, [%0], %1;" ::"r"(peer + full), "r"(bytes + 4) : "memory");
                    asm volatile("st.async.weak.shared::cluster.mbarrier::complete_tx::bytes.b32 [%0], %1, [%2];"
                                 ::"r"(peer + slot), "r"(t), "r"(peer + full) : "memory");
                    if (!valid) return false;
                    asm volatile(
                        "cp.async.bulk.tensor.4d.shared::cluster.global.mbarrier::complete_tx::bytes.multicast::cluster "
                        "[%0], [%1, {%3, %3, %3, %4}], [%2], %5;"
                        ::"r"(sb + s * kStageBytes), "l"(&tm_x), "r"(sb + full), "r"(0), "r"(t * (kTilePx / 8)),
                          "h"((uint16_t)3) : "memory");
                    if (++s == kStages) { s = 0; ph ^= 1; }
                    i++;
                    return true;
                };
                unsigned raw0 = static_tile(2) - nstatic, raw1 = static_tile(3) - nstatic;
#pragma unroll 1
                while (step(raw0) && step(raw1)) {}
#pragma unroll 1
                for (int k = 1; k < kStages; k++) {
                    if (++s == kStages) { s = 0; ph ^= 1; }
                    mbar_wait(sb + kEmptyOff + 8 * s, ph);
                }
            }
        }
    }
}

typedef CUresult (*EncodeTiledFn)(CUtensorMap*, CUtensorMapDataType, cuuint32_t, void*, const cuuint64_t*,
                                  const cuuint64_t*, const cuuint32_t*, const cuuint32_t*, CUtensorMapInterleave,
                                  CUtensorMapSwizzle, CUtensorMapL2promotion, CUtensorMapFloatOOBfill);

}

extern "C" void kernel_launch(void* const* d_in, const int* in_sizes, int n_in, void* d_out, int out_size) {
    (void)n_in; (void)out_size;
    const __nv_bfloat16* x = (const __nv_bfloat16*)d_in[0];
    const __nv_bfloat16* dw = (const __nv_bfloat16*)d_in[1];
    const __nv_bfloat16* pw = (const __nv_bfloat16*)d_in[2];
    const int pixels = in_sizes[0] / kC;

    static EncodeTiledFn encode = nullptr;
    static int grid = 0;
    if (!encode) {
        void* fn = nullptr;
        cudaDriverEntryPointQueryResult qr;
        cudaGetDriverEntryPoint("cuTensorMapEncodeTiled", &fn, cudaEnableDefault, &qr);
        encode = (EncodeTiledFn)fn;
        cudaFuncSetAttribute(dwsep_kernel, cudaFuncAttributeMaxDynamicSharedMemorySize, kSmemBytes);
        int sms = 0, clusters = 0;
        cudaDeviceGetAttribute(&sms, cudaDevAttrMultiProcessorCount, 0);
        cudaLaunchConfig_t cfg = {};
        cudaLaunchAttribute attr = {};
        attr.id = cudaLaunchAttributeClusterDimension;
        attr.val.clusterDim.x = 2;
        attr.val.clusterDim.y = attr.val.clusterDim.z = 1;
        cfg.gridDim = dim3(sms & ~1);
        cfg.blockDim = dim3(kThreads);
        cfg.dynamicSmemBytes = kSmemBytes;
        cfg.attrs = &attr;
        cfg.numAttrs = 1;
        if (cudaOccupancyMaxActiveClusters(&clusters, dwsep_kernel, &cfg) != cudaSuccess || clusters < 1) {
            (void)cudaGetLastError();
            clusters = sms / 2;
        }
        grid = 2 * (clusters < sms / 2 ? clusters : sms / 2);
    }

    CUtensorMap tm_w, tm_x0, tm_x, tm_o, tm_pull;
    auto make_map = [&](CUtensorMap* m, const void* base, int rank, const cuuint64_t* dims, const cuuint64_t* strides,
                        const cuuint32_t* box, CUtensorMapL2promotion promo) {
        const cuuint32_t ones[4] = {1, 1, 1, 1};
        encode(m, CU_TENSOR_MAP_DATA_TYPE_BFLOAT16, rank, (void*)base, dims, strides, box, ones,
               CU_TENSOR_MAP_INTERLEAVE_NONE, CU_TENSOR_MAP_SWIZZLE_128B, promo, CU_TENSOR_MAP_FLOAT_OOB_FILL_NONE);
    };
    {
        const cuuint64_t dims[3] = {64, kC, 6}, strides[2] = {kC * 2, 128};
        const cuuint32_t box[3] = {64, 64, 3};
        make_map(&tm_w, pw, 3, dims, strides, box, CU_TENSOR_MAP_L2_PROMOTION_L2_128B);
    }
    {
        const cuuint64_t dims[4] = {64, 8, 6, (cuuint64_t)pixels / 8}, strides[3] = {kC * 2, 128, kC * 2 * 8};
        const cuuint32_t box0[4] = {64, 8, 2, 8}, box[4] = {64, 8, 6, kTilePx / 8};
        make_map(&tm_x0, x, 4, dims, strides, box0, CU_TENSOR_MAP_L2_PROMOTION_L2_128B);
        make_map(&tm_x, x, 4, dims, strides, box, CU_TENSOR_MAP_L2_PROMOTION_L2_128B);
    }
    {
        const cuuint64_t dims[3] = {64, 6, (cuuint64_t)pixels}, strides[2] = {128, kC * 2};
        const cuuint32_t box[3] = {64, 3, kTilePx};
        make_map(&tm_o, d_out, 3, dims, strides, box, CU_TENSOR_MAP_L2_PROMOTION_NONE);
    }
    {
        const cuuint64_t dims[2] = {64, (cuuint64_t)pixels * 6}, strides[1] = {128};
        const cuuint32_t box[2] = {8, 192}, ones[2] = {1, 1};
        encode(&tm_pull, CU_TENSOR_MAP_DATA_TYPE_BFLOAT16, 2, (void*)x, dims, strides, box, ones, CU_TENSOR_MAP_INTERLEAVE_NONE,
               CU_TENSOR_MAP_SWIZZLE_NONE, CU_TENSOR_MAP_L2_PROMOTION_L2_128B, CU_TENSOR_MAP_FLOAT_OOB_FILL_NONE);
    }
    Knobs kn = g_knobs;
    for (int k = 0; k < kLeadPts; k++)
        kn.lead_slope[k] = k < kLeadPts - 1 ? (kn.lead[k + 1] - kn.lead[k]) * 65536 / (kn.lead_pos[k + 1] - kn.lead_pos[k]) : 0;
    dwsep_kernel<<<grid, kThreads, kSmemBytes, cudaStreamPerThread>>>(tm_w, tm_x0, tm_x, tm_o, tm_pull, x, dw, pw,
                                                                      pixels / kTilePx, kn);
}
```

```cpp
#include <cuda_runtime.h>
#include <cuda_bf16.h>
#include <cuda.h>
#include <stdint.h>

namespace {

constexpr int kC = 384;
constexpr int kTilePx = 32;
constexpr int kStages = 5;
constexpr int kOutBufs = 8;
constexpr int kPark = 5;
constexpr int kThreads = 512;
constexpr int kStageBytes = kTilePx * kC * 2;
constexpr int kOutBytes = kTilePx * 192 * 2;
constexpr int kWChunkBytes = 64 * 192 * 2;
constexpr int kXSlabBytes = 64 * 128 * 2;
constexpr int kWOff = 3 * kStageBytes;
constexpr int kOutOff = kStages * kStageBytes;
constexpr int kSpillOff = kOutOff + kOutBufs * kOutBytes;
constexpr int kDwOff = kSpillOff;
constexpr int kScratchOff = kSpillOff + 1024;
constexpr int kFullOff = kSpillOff + 384 * 28;
constexpr int kEmptyOff = kFullOff + 8 * kStages;
constexpr int kOFullOff = kEmptyOff + 8 * kStages;
constexpr int kOEmptyOff = kOFullOff + 8 * kOutBufs;
constexpr int kWBarOff = kOEmptyOff + 8 * kOutBufs;
constexpr int kXBarOff = kWBarOff + 8 * 3;
constexpr int kDwBarOff = kXBarOff + 8 * 3;
constexpr int kPullBarOff = kDwBarOff + 8;
constexpr int kSlotOff = kPullBarOff + 8;
constexpr int kOSlotOff = kSlotOff + 4 * kStages;
constexpr int kPSlotOff = kOSlotOff + 4 * kOutBufs;
constexpr int kSmemBytes = kPSlotOff + 4 * (kPark + 1);
static_assert(kWChunkBytes == kStageBytes && kWOff + 6 * kWChunkBytes <= kDwOff, "weight staging");
static_assert(kSmemBytes <= 232448, "shared memory");

constexpr int kHoldPts = 8, kLeadPts = 10;
struct Knobs {
    int first_gap;
    int pull_n, pull_t0, pull_dt;
    int pf_from, pf_t0, pf_dt;
    int static_tiles;
    int mid_from, mid_to, mid_n;
    int park_from;
    int stream_from;
    int hold_pos[kHoldPts], hold[kHoldPts];
    int lead_pos[kLeadPts], lead[kLeadPts];
    int lead_slope[kLeadPts];
};
#define DEFAULT_KNOBS {455, 5, 70, 490, 561, 70, 700, 18, 1601, 3150, 2, 3416, 4395, \
    {0, 451, 721, 1081, 2000, 3000, 4262, 4608}, {0, 1, 2, 3, 3, 3, 1, 1}, \
    {0, 819, 1484, 1900, 2100, 2310, 3475, 3800, 4200, 4490}, {330, 365, 544, 372, 355, 355, 88, 180, 200, 169}}
constexpr Knobs g_knobs = DEFAULT_KNOBS;

__device__ unsigned int g_tile_counter;

__device__ __forceinline__ uint32_t smem_u32(const void* p) { return (uint32_t)__cvta_generic_to_shared(p); }

__device__ __forceinline__ void mbar_init(uint32_t bar, uint32_t cnt) {
    asm volatile("mbarrier.init.shared::cta.b64 [%0], %1;" ::"r"(bar), "r"(cnt) : "memory");
}
__device__ __forceinline__ void mbar_expect_tx(uint32_t bar, uint32_t bytes) {
    asm volatile("mbarrier.arrive.expect_tx.shared::cta.b64 _, [%0], %1;" ::"r"(bar), "r"(bytes) : "memory");
}
__device__ __forceinline__ void mbar_arrive(uint32_t bar) {
    asm volatile("mbarrier.arrive.shared::cta.b64 _, [%0];" ::"r"(bar) : "memory");
}
__device__ __forceinline__ void mbar_arrive_cluster(uint32_t bar) {
    asm volatile("mbarrier.arrive.shared::cluster.b64 _, [%0];" ::"r"(bar) : "memory");
}
__device__ __forceinline__ void mbar_wait(uint32_t bar, uint32_t parity) {
    asm volatile(
        "{\n.reg .pred p;\n.reg .u32 n;\n"
        "mbarrier.try_wait.parity.shared::cta.b64 p, [%0], %1;\n"
        "@p bra DONE;\n"
        "mov.u32 n, 0;\n"
        "LOOP:\n"
        "mbarrier.try_wait.parity.shared::cta.b64 p, [%0], %1;\n"
        "@p bra DONE;\n"
        "add.u32 n, n, 1;\n"
        "setp.lt.u32 p, n, 4194304;\n"
        "@p bra LOOP;\n"
        "trap;\n"
        "DONE:\n}" ::"r"(bar), "r"(parity) : "memory");
}
__device__ __forceinline__ uint32_t map_to_cta(uint32_t addr, uint32_t cta) {
    uint32_t r;
    asm("mapa.shared::cluster.u32 %0, %1, %2;" : "=r"(r) : "r"(addr), "r"(cta));
    return r;
}
__device__ __forceinline__ void named_bar_sync(int id, int n) { asm volatile("bar.sync %0, %1;" ::"r"(id), "r"(n) : "memory"); }
__device__ __forceinline__ void named_bar_arrive(int id, int n) { asm volatile("bar.arrive %0, %1;" ::"r"(id), "r"(n) : "memory"); }
__device__ __forceinline__ void cluster_arrive() {
    __syncwarp();
    asm volatile("barrier.cluster.arrive.relaxed.aligned;" ::: "memory");
}
__device__ __forceinline__ void cluster_wait() {
    __syncwarp();
    asm volatile("barrier.cluster.wait.acquire.aligned;" ::: "memory");
}
__device__ __forceinline__ void prefetch_line(const void* p) { asm volatile("prefetch.global.L2 [%0];" ::"l"(p) : "memory"); }
__device__ __forceinline__ void prefetch_map(const CUtensorMap* m) { asm volatile("prefetch.tensormap [%0];" ::"l"(m) : "memory"); }
__device__ __forceinline__ uint32_t globaltimer() {
    uint32_t t;
    asm volatile("mov.u32 %0, %%globaltimer_lo;" : "=r"(t));
    return t;
}
__device__ __forceinline__ uint32_t clock32() {
    uint32_t t;
    asm volatile("mov.u32 %0, %%clock;" : "=r"(t));
    return t;
}
__device__ __forceinline__ int lds32(uint32_t addr) {
    int v;
    asm volatile("ld.shared.b32 %0, [%1];" : "=r"(v) : "r"(addr) : "memory");
    return v;
}
__device__ __forceinline__ int lds32_volatile(uint32_t addr) {
    int v;
    asm volatile("ld.volatile.shared.b32 %0, [%1];" : "=r"(v) : "r"(addr) : "memory");
    return v;
}
__device__ __forceinline__ void sts32(uint32_t addr, int v) { asm volatile("st.shared.b32 [%0], %1;" ::"r"(addr), "r"(v) : "memory"); }

#define ACC4(o) "+f"(d[o]), "+f"(d[o + 1]), "+f"(d[o + 2]), "+f"(d[o + 3])
#define ACC16(o) ACC4(o), ACC4(o + 4), ACC4(o + 8), ACC4(o + 12)
__device__ __forceinline__ void wgmma_rs(float (&d)[32], const uint32_t (&a)[4], uint64_t desc_b, int scale_d) {
    asm volatile(
        "{\n.reg .pred p;\nsetp.ne.b32 p, %37, 0;\n"
        "wgmma.mma_async.sync.aligned.m64n64k16.f32.bf16.bf16 "
        "{%0, %1, %2, %3, %4, %5, %6, %7, %8, %9, %10, %11, %12, %13, %14, %15, "
        "%16, %17, %18, %19, %20, %21, %22, %23, %24, %25, %26, %27, %28, %29, %30, %31}, "
        "{%32, %33, %34, %35}, %36, p, 1, 1, 0;\n}"
        : ACC16(0), ACC16(16)
        : "r"(a[0]), "r"(a[1]), "r"(a[2]), "r"(a[3]), "l"(desc_b), "r"(scale_d));
}
__device__ __forceinline__ void wgmma_rs(float (&d)[16], const uint32_t (&a)[4], uint64_t desc_b, int scale_d) {
    asm volatile(
        "{\n.reg .pred p;\nsetp.ne.b32 p, %21, 0;\n"
        "wgmma.mma_async.sync.aligned.m64n32k16.f32.bf16.bf16 "
        "{%0, %1, %2, %3, %4, %5, %6, %7, %8, %9, %10, %11, %12, %13, %14, %15}, "
        "{%16, %17, %18, %19}, %20, p, 1, 1, 0;\n}"
        : ACC16(0)
        : "r"(a[0]), "r"(a[1]), "r"(a[2]), "r"(a[3]), "l"(desc_b), "r"(scale_d));
}
__device__ __forceinline__ uint64_t make_desc(uint32_t addr, uint32_t group_stride) {
    return (uint64_t(1) << 62) | (uint64_t(group_stride >> 4) << 32) | (uint64_t(1) << 16) | (uint64_t)((addr & 0x3FFFF) >> 4);
}
__device__ __forceinline__ constexpr uint64_t desc_k(int k) { return (uint64_t)(((k >> 2) * 1024 + (k & 3) * 32) >> 4); }

__device__ __forceinline__ uint32_t pack_bf16(float lo, float hi) {
    uint32_t r;
    asm("cvt.rn.bf16x2.f32 %0, %1, %2;" : "=r"(r) : "f"(hi), "f"(lo));
    return r;
}
__device__ __forceinline__ uint32_t mul_bf16x2(uint32_t a, uint32_t b) {
    uint32_t r;
    asm("mul.rn.bf16x2 %0, %1, %2;" : "=r"(r) : "r"(a), "r"(b));
    return r;
}

__global__ void __cluster_dims__(2, 1, 1) __launch_bounds__(kThreads, 1)
dwsep_kernel(const __grid_constant__ CUtensorMap tm_w, const __grid_constant__ CUtensorMap tm_x0,
             const __grid_constant__ CUtensorMap tm_x, const __grid_constant__ CUtensorMap tm_o,
             const __grid_constant__ CUtensorMap tm_pull,
             const __nv_bfloat16* __restrict__ x, const __nv_bfloat16* __restrict__ dw,
             const __nv_bfloat16* __restrict__ pw, int num_tiles,
             int mid_from, int mid_to, int mid_n, int park_from,
             const __grid_constant__ Knobs kn) {
    extern __shared__ __align__(1024) uint8_t smem_raw[];
    const uint32_t sb = smem_u32(smem_raw);

    uint32_t rank;
    asm("mov.u32 %0, %%cluster_ctarank;" : "=r"(rank));
    const int cluster = blockIdx.x >> 1;
    auto static_tile = [&](int i) { return (i >> 1) * gridDim.x + cluster * 2 + (i & 1); };

    if (threadIdx.x < 32) {
        prefetch_line(threadIdx.x < 18 ? (const char*)pw + (blockIdx.x & 127) * 2304 + threadIdx.x * 128
                                       : (const char*)dw + min(threadIdx.x - 18, 5) * 128);
    } else if (threadIdx.x < 224) {
        const uint32_t c0 = __shfl_sync(0xffffffffu, clock32(), 0), chunk = (threadIdx.x >> 5) - 1;
        const uint32_t delay = ((chunk >> 1) * gridDim.x + blockIdx.x) * kn.first_gap >> 7;
        for (int n = 0; clock32() - c0 < delay && n < 1024; n++) {}
        prefetch_line((const char*)x + (size_t)blockIdx.x * kStageBytes + (threadIdx.x & 31) * 768 + chunk * 128);
    } else if (threadIdx.x == 288) {
        prefetch_map(&tm_w);
        prefetch_map(&tm_x0);
        if (rank == 1) prefetch_map(&tm_pull);
    }
    if (threadIdx.x >> 5 == 8) {
        if (threadIdx.x == 256) {
#pragma unroll
            for (int b = 0; b < 7; b++) mbar_init(sb + kWBarOff + 8 * b, 1);
            asm volatile("fence.proxy.async.shared::cta;" ::: "memory");
        }
        __syncwarp();
        named_bar_arrive(8, 384);
        if (threadIdx.x == 256) {
            mbar_expect_tx(sb + kDwBarOff, kC * 2);
            asm volatile("cp.async.bulk.shared::cluster.global.mbarrier::complete_tx::bytes [%0], [%1], %2, [%3];"
                         ::"r"(sb + kDwOff), "l"(dw), "r"(kC * 2), "r"(sb + kDwBarOff) : "memory");
#pragma unroll
            for (int j = 0; j < 3; j++) {
                mbar_expect_tx(sb + kWBarOff + 8 * j, 2 * kWChunkBytes);
#pragma unroll
                for (int c = 2 * j; c < 2 * j + 2; c++)
                    asm volatile("cp.async.bulk.tensor.3d.shared::cluster.global.mbarrier::complete_tx::bytes [%0], [%1, {%3, %4, %5}], [%2];"
                                 ::"r"(sb + kWOff + c * kWChunkBytes), "l"(&tm_w), "r"(sb + kWBarOff + 8 * j), "r"(0), "r"(c * 64),
                                   "r"((int)rank * 3) : "memory");
                mbar_expect_tx(sb + kXBarOff + 8 * j, kXSlabBytes);
                asm volatile("cp.async.bulk.tensor.4d.shared::cluster.global.mbarrier::complete_tx::bytes [%0], [%1, {%3, %3, %4, %5}], [%2];"
                             ::"r"(sb + j * kXSlabBytes), "l"(&tm_x0), "r"(sb + kXBarOff + 8 * j), "r"(0), "r"(2 * j),
                               "r"(cluster * 8) : "memory");
            }
        }
        __syncwarp();
    }

    if (threadIdx.x < 384) {
        asm volatile("setmaxnreg.inc.sync.aligned.u32 160;");
        cluster_arrive();
        if (threadIdx.x >> 5 != 8) named_bar_sync(8, 384);
        const int wg = __shfl_sync(0xffffffffu, threadIdx.x >> 7, 0);
        const int warp = (threadIdx.x >> 5) & 3;
        const int lane = threadIdx.x & 31;
        const int mi = lane >> 3, ri = lane & 7;
        const uint32_t leader_empty = map_to_cta(sb + kEmptyOff, 0);
        uint32_t st_off = sb + kOutOff + (((mi >> 1) * 8 + ri) * 3 + wg) * 128 + (((2 * warp + (mi & 1)) ^ ((3 * ri + wg) & 7)) << 4);
        int s = 0, ob = 0;
        uint32_t ph = 0, oph = 1;
        auto release_stage = [&]() {
            if (lane == 0) mbar_arrive_cluster(leader_empty + 8 * s);
            if (++s == kStages) { s = 0; ph ^= 1; }
        };
        auto pack = [&](uint32_t (&p)[8], const float* acc) {
#pragma unroll
            for (int k = 0; k < 8; k++) p[k] = pack_bf16(acc[2 * k], acc[2 * k + 1]);
        };
        auto put = [&](const uint32_t (&p)[8], int t) {
            mbar_wait(sb + kOEmptyOff + 8 * ob, oph);
            if (threadIdx.x == 0) sts32(sb + kOSlotOff + 4 * ob, t);
#pragma unroll
            for (int q = 0; q < 2; q++)
                asm volatile("stmatrix.sync.aligned.m8n8.x4.trans.shared.b16 [%0], {%1, %2, %3, %4};"
                             ::"r"(st_off + ob * kOutBytes + q * (16 * 384)), "r"(p[4 * q]), "r"(p[4 * q + 1]),
                               "r"(p[4 * q + 2]), "r"(p[4 * q + 3]) : "memory");
            asm volatile("fence.proxy.async.shared::cta;" ::: "memory");
            __syncwarp();
            if (lane == 0) mbar_arrive(sb + kOFullOff + 8 * ob);
            if (++ob == kOutBufs) { ob = 0; oph ^= 1; }
        };
        auto my_turn = [&]() { named_bar_sync(2 + wg, 256); };
        auto pass_turn = [&]() { named_bar_arrive(wg == 2 ? 2 : 3 + wg, 256); };
        if (wg == 2) pass_turn();

        uint32_t a[24][4];
        {
            float acc0[32];
            uint32_t dws[48];
            mbar_wait(sb + kDwBarOff, 0);
#pragma unroll
            for (int k = 0; k < 48; k++) dws[k] = lds32(sb + kDwOff + k * 16 + (lane & 3) * 4);
            cluster_wait();
            if (lane < 3) mbar_arrive_cluster(leader_empty + 8 * lane);
            const uint32_t wbase = sb + kWOff + wg * 8192 + ((mi >> 1) * 8 + ri) * 128 + (((2 * warp + (mi & 1)) ^ ri) << 4);
            const uint64_t desc = make_desc(sb, 2048);
#pragma unroll
            for (int j = 0; j < 3; j++) {
                mbar_wait(sb + kWBarOff + 8 * j, 0);
#pragma unroll
                for (int k = 8 * j; k < 8 * j + 8; k++) {
                    asm volatile("ldmatrix.sync.aligned.m8n8.x4.trans.shared.b16 {%0, %1, %2, %3}, [%4];"
                                 : "=r"(a[k][0]), "=r"(a[k][1]), "=r"(a[k][2]), "=r"(a[k][3])
                                 : "r"(wbase + (k >> 2) * kWChunkBytes + (k & 3) * 2048) : "memory");
                    a[k][0] = mul_bf16x2(a[k][0], dws[2 * k]);
                    a[k][1] = mul_bf16x2(a[k][1], dws[2 * k]);
                    a[k][2] = mul_bf16x2(a[k][2], dws[2 * k + 1]);
                    a[k][3] = mul_bf16x2(a[k][3], dws[2 * k + 1]);
                }
                uint32_t dep = 0;
#pragma unroll
                for (int k = 8 * j; k < 8 * j + 8; k++) dep ^= a[k][3];
                dep &= num_tiles >> 24;
                if (j == 0 && lane >= 3 && lane < kStages) mbar_arrive_cluster(leader_empty + 8 * lane + dep);
                if (j == 2) {
                    named_bar_arrive((wg == 0 ? 6 : 5) + dep, 384);
                    named_bar_arrive(wg == 2 ? 6 : 7, 384);
                }
                mbar_wait(sb + kXBarOff + 8 * j, 0);
                my_turn();
                asm volatile("wgmma.fence.sync.aligned;" ::: "memory");
#pragma unroll
                for (int k = 0; k < 8; k++) wgmma_rs(acc0, a[8 * j + k], desc + (j * kXSlabBytes >> 4) + desc_k(k), j + k != 0);
                pass_turn();
            }
            asm volatile("wgmma.commit_group.sync.aligned;" ::: "memory");
            named_bar_sync(5 + wg, 384);
            asm volatile("wgmma.wait_group.sync.aligned 0;" ::: "memory");
            release_stage();
            release_stage();
            uint32_t p[8];
            pack(p, acc0);
            put(p, static_tile(0));
            pack(p, acc0 + 16);
            put(p, static_tile(1));
        }

        float acc[16];
        uint32_t park[kPark][8], park_last;
        int parked = 0;
        st_off += num_tiles >> 24;
        auto spill_addr = [&](int base, int shift, int zero) {
            return ((st_off + zero) >> shift) + (sb - (sb >> shift) + kSpillOff + base - (kOutOff >> shift));
        };
        asm volatile("mov.b32 %0, 0;" : "=r"(park_last));
#pragma unroll
        for (int k = 0; k < kPark * 8; k++) asm volatile("mov.b32 %0, 0;" : "=r"(park[k / 8][k % 8]));
#pragma unroll 1
        while (true) {
            mbar_wait(sb + kFullOff + 8 * s, ph);
            const int t = lds32(sb + kSlotOff + 4 * s);
            if (t >= num_tiles) break;
            const uint64_t desc = make_desc(sb + s * kStageBytes, 6144);
            my_turn();
            asm volatile("wgmma.fence.sync.aligned;" ::: "memory");
#pragma unroll
            for (int k = 0; k < 24; k++) {
                if (k == 19) pass_turn();
                wgmma_rs(acc, a[k], desc + desc_k(k), k != 0);
            }
            asm volatile("wgmma.commit_group.sync.aligned;" ::: "memory");
            asm volatile("wgmma.wait_group.sync.aligned 0;" ::: "memory");
            release_stage();
            const int keep = t >= park_from ? kPark + 1 : t >= mid_from && t < mid_to ? mid_n : 0;
            if (parked < keep) {
#pragma unroll
                for (int k = 0; k < kPark; k++)
                    if (parked == k) pack(park[k], acc);
                if (parked == kPark) {
                    uint32_t p[8];
                    pack(p, acc);
                    mbar_wait(sb + kPullBarOff, 0);
                    asm volatile("st.shared.v4.b32 [%0], {%1, %2, %3, %4};"
                                 ::"r"(spill_addr(0, 0, 0)), "r"(p[0]), "r"(p[1]), "r"(p[2]), "r"(p[3]) : "memory");
                    asm volatile("st.shared.v2.b32 [%0], {%1, %2};" ::"r"(spill_addr(6144, 1, t >> 24)), "r"(p[4]), "r"(p[5]) : "memory");
                    sts32(spill_addr(9216, 2, t >> 24), p[6]);
                    asm volatile("xor.b32 %0, %1, %2;" : "=r"(park_last) : "r"(p[7]), "r"(st_off));
                }
                if (threadIdx.x == 0) sts32(sb + kPSlotOff + 4 * parked, t);
                parked++;
            } else {
                uint32_t p[8];
                pack(p, acc);
                put(p, t);
                if (parked > keep) {
#pragma unroll
                    for (int k = 2; k >= 0; k--)
                        if (k < parked) put(park[k], threadIdx.x == 0 ? lds32(sb + kPSlotOff + 4 * k) : 0);
                    parked = 0;
                }
            }
        }
#pragma unroll
        for (int k = 0; k < kPark; k++)
            if (k < parked) put(park[k], threadIdx.x == 0 ? lds32(sb + kPSlotOff + 4 * k) : 0);
        if (parked > kPark) {
            uint32_t p[8];
            asm volatile("ld.shared.v4.b32 {%0, %1, %2, %3}, [%4];"
                         : "=r"(p[0]), "=r"(p[1]), "=r"(p[2]), "=r"(p[3]) : "r"(spill_addr(0, 0, 0)) : "memory");
            asm volatile("ld.shared.v2.b32 {%0, %1}, [%2];" : "=r"(p[4]), "=r"(p[5]) : "r"(spill_addr(6144, 1, parked >> 24)) : "memory");
            p[6] = lds32(spill_addr(9216, 2, parked >> 24));
            asm volatile("xor.b32 %0, %1, %2;" : "=r"(p[7]) : "r"(park_last), "r"(st_off));
            put(p, threadIdx.x == 0 ? lds32(sb + kPSlotOff + 4 * kPark) : 0);
        }
        mbar_wait(sb + kPullBarOff, 0);
#pragma unroll 1
        for (int k = 0; k < 2; k++) {
            mbar_wait(sb + kOEmptyOff + 8 * ob, oph);
            if (threadIdx.x == 0) sts32(sb + kOSlotOff + 4 * ob, num_tiles);
            if (lane == 0) mbar_arrive(sb + kOFullOff + 8 * ob);
            if (++ob == kOutBufs) { ob = 0; oph ^= 1; }
        }
    } else {
        asm volatile("setmaxnreg.dec.sync.aligned.u32 32;");
        const int role = (threadIdx.x >> 5) & 3;
        const bool lead = (threadIdx.x & 31) == 0;
        if (role >= 2) {
            const int par = role & 1;
            if (lead) {
                if (par == 0) {
#pragma unroll
                    for (int b = 0; b < kOutBufs; b++) {
                        mbar_init(sb + kOFullOff + 8 * b, 12);
                        mbar_init(sb + kOEmptyOff + 8 * b, 1);
                    }
                } else {
#pragma unroll
                    for (int s = 0; s < kStages; s++) {
                        mbar_init(sb + kFullOff + 8 * s, 1);
                        mbar_init(sb + kEmptyOff + 8 * s, 24);
                        if (s < 2) mbar_arrive(sb + kFullOff + 8 * s);
                    }
                    prefetch_map(&tm_x);
                    prefetch_map(&tm_o);
                }
                asm volatile("fence.mbarrier_init.release.cluster;" ::: "memory");
            }
            cluster_arrive();
            cluster_wait();
            if (lead) {
                uint64_t normal, streaming;
                asm volatile("createpolicy.fractional.L2::evict_normal.b64 %0, 1.0;" : "=l"(normal));
                asm volatile("createpolicy.fractional.L2::evict_first.b64 %0, 1.0;" : "=l"(streaming));
                int head = par, tail = par, held = 0, pos = 0, k = 0, hold = 0;
                uint32_t ph = 0;
#pragma unroll 1
                while (true) {
                    mbar_wait(sb + kOFullOff + 8 * head, ph);
                    const int t = lds32(sb + kOSlotOff + 4 * head);
                    if (t < num_tiles) {
                        held++;
                        pos = max(pos, t);
                        if ((head += 2) >= kOutBufs) { head = par; ph ^= 1; }
#pragma unroll 1
                        for (; k < kHoldPts && pos >= kn.hold_pos[k]; k++) hold = kn.hold[k];
                    } else {
                        hold = 0;
                    }
                    int freed = tail, n = 0;
#pragma unroll 1
                    for (; held > hold; held--, n++) {
                        asm volatile("cp.async.bulk.tensor.3d.global.shared::cta.bulk_group.L2::cache_hint [%0, {%2, %3, %4}], [%1], %5;"
                                     ::"l"(&tm_o), "r"(sb + kOutOff + tail * kOutBytes), "r"(0), "r"((int)rank * 3),
                                       "r"(lds32(sb + kOSlotOff + 4 * tail) * kTilePx),
                                       "l"(pos >= kn.stream_from ? streaming : normal) : "memory");
                        asm volatile("cp.async.bulk.commit_group;" ::: "memory");
                        if ((tail += 2) >= kOutBufs) tail = par;
                    }
#pragma unroll 1
                    while (n-- > 0) {
                        if (n == 0) asm volatile("cp.async.bulk.wait_group.read 0;" ::: "memory");
                        else if (n == 1) asm volatile("cp.async.bulk.wait_group.read 1;" ::: "memory");
                        else if (n == 2) asm volatile("cp.async.bulk.wait_group.read 2;" ::: "memory");
                        else asm volatile("cp.async.bulk.wait_group.read 3;" ::: "memory");
                        mbar_arrive(sb + kOEmptyOff + 8 * freed);
                        if ((freed += 2) >= kOutBufs) freed = par;
                    }
                    if (t >= num_tiles) break;
                }
            }
        } else if (role == 1) {
            const uint32_t t_start = __shfl_sync(0xffffffffu, globaltimer(), 0);
            const uint32_t my_slot = sb + kSlotOff + 4 * min(threadIdx.x & 31, kStages - 1);
            sts32(my_slot, 0);
            __threadfence_block();
            cluster_arrive();
            int k = 0;
#pragma unroll 1
            for (int t = blockIdx.x + gridDim.x; t < num_tiles; t += gridDim.x) {
                if (t < kn.pf_from) continue;
                const uint32_t due = kn.pf_t0 + (t - gridDim.x) * kn.pf_dt / gridDim.x;
                for (int n = 0; globaltimer() - t_start < due && n < 4096; n++) __nanosleep(50);
#pragma unroll 1
                while (k + 1 < kLeadPts && t >= kn.lead_pos[k + 1]) k++;
                const int max_lead = kn.lead[k] + ((t - kn.lead_pos[k]) * kn.lead_slope[k] >> 16);
                for (int n = 0; t > max_lead && n < 4096; n++) {
                    const int front = __reduce_max_sync(0xffffffffu, lds32_volatile(my_slot));
                    if (t - max_lead <= front || front >= num_tiles) break;
                    __nanosleep(50);
                }
                if (lead)
                    asm volatile("cp.async.bulk.prefetch.L2.global [%0], %1;"
                                 ::"l"((const char*)x + (size_t)t * kStageBytes), "r"(kStageBytes) : "memory");
            }
            cluster_wait();
        } else {
            const uint32_t t_start = __shfl_sync(0xffffffffu, globaltimer(), 0);
            if (lead) {
                mbar_init(sb + kPullBarOff, 1);
                asm volatile("fence.proxy.async.shared::cta;" ::: "memory");
                mbar_expect_tx(sb + kPullBarOff, rank * 3072 * kn.pull_n);
            }
            __threadfence_block();
            cluster_arrive();
            if (rank == 1 && lead) {
#pragma unroll 1
                for (int i = 0; i < kn.pull_n; i++) {
                    const uint32_t due = kn.pull_t0 + (i * gridDim.x + blockIdx.x) * kn.pull_dt / gridDim.x;
                    for (int n = 0; globaltimer() - t_start < due && n < 4096; n++) {}
                    asm volatile("cp.async.bulk.tensor.2d.shared::cluster.global.mbarrier::complete_tx::bytes [%0], [%1, {%3, %4}], [%2];"
                                 ::"r"(sb + kScratchOff), "l"(&tm_pull), "r"(sb + kPullBarOff), "r"(0), "r"(static_tile(i + 2) * 192) : "memory");
                }
            }
            cluster_wait();
            if (lead && rank == 0) {
                const uint32_t peer = map_to_cta(sb, 1);
                const int nstatic = kn.static_tiles * (gridDim.x >> 1);
                const unsigned last_fetch = num_tiles - nstatic + gridDim.x - 1;
                mbar_wait(sb + kEmptyOff, 0);
                mbar_wait(sb + kEmptyOff + 8, 0);
                int s = 2, i = 2;
                uint32_t ph = 0;
                auto step = [&](unsigned& raw) -> bool {
                    const int t = nstatic + raw;
                    const bool valid = t < num_tiles;
                    raw = static_tile(i + 2) - nstatic;
                    if (i + 2 >= kn.static_tiles && valid)
                        asm volatile("atom.global.inc.u32 %0, [%1], %2;" : "+r"(raw) : "l"(&g_tile_counter), "r"(last_fetch) : "memory");
                    mbar_wait(sb + kEmptyOff + 8 * s, ph);
                    const uint32_t full = kFullOff + 8 * s, slot = kSlotOff + 4 * s;
                    const uint32_t bytes = valid ? kStageBytes : 0;
                    sts32(sb + slot, t);
                    mbar_expect_tx(sb + full, bytes);
                    asm volatile("mbarrier.arrive.expect_tx.shared::cluster.b64 _, [%0], %1;" ::"r"(peer + full), "r"(bytes + 4) : "memory");
                    asm volatile("st.async.weak.shared::cluster.mbarrier::complete_tx::bytes.b32 [%0], %1, [%2];"
                                 ::"r"(peer + slot), "r"(t), "r"(peer + full) : "memory");
                    if (!valid) return false;
                    asm volatile(
                        "cp.async.bulk.tensor.4d.shared::cluster.global.mbarrier::complete_tx::bytes.multicast::cluster "
                        "[%0], [%1, {%3, %3, %3, %4}], [%2], %5;"
                        ::"r"(sb + s * kStageBytes), "l"(&tm_x), "r"(sb + full), "r"(0), "r"(t * (kTilePx / 8)),
                          "h"((uint16_t)3) : "memory");
                    if (++s == kStages) { s = 0; ph ^= 1; }
                    i++;
                    return true;
                };
                unsigned raw0 = static_tile(2) - nstatic, raw1 = static_tile(3) - nstatic;
#pragma unroll 1
                while (step(raw0) && step(raw1)) {}
#pragma unroll 1
                for (int k = 1; k < kStages; k++) {
                    if (++s == kStages) { s = 0; ph ^= 1; }
                    mbar_wait(sb + kEmptyOff + 8 * s, ph);
                }
            }
        }
    }
}

typedef CUresult (*EncodeTiledFn)(CUtensorMap*, CUtensorMapDataType, cuuint32_t, void*, const cuuint64_t*,
                                  const cuuint64_t*, const cuuint32_t*, const cuuint32_t*, CUtensorMapInterleave,
                                  CUtensorMapSwizzle, CUtensorMapL2promotion, CUtensorMapFloatOOBfill);

}

extern "C" void kernel_launch(void* const* d_in, const int* in_sizes, int n_in, void* d_out, int out_size) {
    (void)n_in; (void)out_size;
    const __nv_bfloat16* x = (const __nv_bfloat16*)d_in[0];
    const __nv_bfloat16* dw = (const __nv_bfloat16*)d_in[1];
    const __nv_bfloat16* pw = (const __nv_bfloat16*)d_in[2];
    const int pixels = in_sizes[0] / kC;

    static EncodeTiledFn encode = nullptr;
    static int grid = 0;
    if (!encode) {
        void* fn = nullptr;
        cudaDriverEntryPointQueryResult qr;
        cudaGetDriverEntryPoint("cuTensorMapEncodeTiled", &fn, cudaEnableDefault, &qr);
        encode = (EncodeTiledFn)fn;
        cudaFuncSetAttribute(dwsep_kernel, cudaFuncAttributeMaxDynamicSharedMemorySize, kSmemBytes);
        int sms = 0, clusters = 0;
        cudaDeviceGetAttribute(&sms, cudaDevAttrMultiProcessorCount, 0);
        cudaLaunchConfig_t cfg = {};
        cudaLaunchAttribute attr = {};
        attr.id = cudaLaunchAttributeClusterDimension;
        attr.val.clusterDim.x = 2;
        attr.val.clusterDim.y = attr.val.clusterDim.z = 1;
        cfg.gridDim = dim3(sms & ~1);
        cfg.blockDim = dim3(kThreads);
        cfg.dynamicSmemBytes = kSmemBytes;
        cfg.attrs = &attr;
        cfg.numAttrs = 1;
        if (cudaOccupancyMaxActiveClusters(&clusters, dwsep_kernel, &cfg) != cudaSuccess || clusters < 1) {
            (void)cudaGetLastError();
            clusters = sms / 2;
        }
        grid = 2 * (clusters < sms / 2 ? clusters : sms / 2);
    }

    CUtensorMap tm_w, tm_x0, tm_x, tm_o, tm_pull;
    auto make_map = [&](CUtensorMap* m, const void* base, int rank, const cuuint64_t* dims, const cuuint64_t* strides,
                        const cuuint32_t* box, CUtensorMapL2promotion promo) {
        const cuuint32_t ones[4] = {1, 1, 1, 1};
        encode(m, CU_TENSOR_MAP_DATA_TYPE_BFLOAT16, rank, (void*)base, dims, strides, box, ones,
               CU_TENSOR_MAP_INTERLEAVE_NONE, CU_TENSOR_MAP_SWIZZLE_128B, promo, CU_TENSOR_MAP_FLOAT_OOB_FILL_NONE);
    };
    {
        const cuuint64_t dims[3] = {64, kC, 6}, strides[2] = {kC * 2, 128};
        const cuuint32_t box[3] = {64, 64, 3};
        make_map(&tm_w, pw, 3, dims, strides, box, CU_TENSOR_MAP_L2_PROMOTION_L2_128B);
    }
    {
        const cuuint64_t dims[4] = {64, 8, 6, (cuuint64_t)pixels / 8}, strides[3] = {kC * 2, 128, kC * 2 * 8};
        const cuuint32_t box0[4] = {64, 8, 2, 8}, box[4] = {64, 8, 6, kTilePx / 8};
        make_map(&tm_x0, x, 4, dims, strides, box0, CU_TENSOR_MAP_L2_PROMOTION_L2_128B);
        make_map(&tm_x, x, 4, dims, strides, box, CU_TENSOR_MAP_L2_PROMOTION_L2_128B);
    }
    {
        const cuuint64_t dims[3] = {64, 6, (cuuint64_t)pixels}, strides[2] = {128, kC * 2};
        const cuuint32_t box[3] = {64, 3, kTilePx};
        make_map(&tm_o, d_out, 3, dims, strides, box, CU_TENSOR_MAP_L2_PROMOTION_NONE);
    }
    {
        const cuuint64_t dims[2] = {64, (cuuint64_t)pixels * 6}, strides[1] = {128};
        const cuuint32_t box[2] = {8, 192}, ones[2] = {1, 1};
        encode(&tm_pull, CU_TENSOR_MAP_DATA_TYPE_BFLOAT16, 2, (void*)x, dims, strides, box, ones, CU_TENSOR_MAP_INTERLEAVE_NONE,
               CU_TENSOR_MAP_SWIZZLE_NONE, CU_TENSOR_MAP_L2_PROMOTION_L2_128B, CU_TENSOR_MAP_FLOAT_OOB_FILL_NONE);
    }
    Knobs kn = g_knobs;
    for (int k = 0; k < kLeadPts; k++)
        kn.lead_slope[k] = k < kLeadPts - 1 ? (kn.lead[k + 1] - kn.lead[k]) * 65536 / (kn.lead_pos[k + 1] - kn.lead_pos[k]) : 0;
    dwsep_kernel<<<grid, kThreads, kSmemBytes, cudaStreamPerThread>>>(tm_w, tm_x0, tm_x, tm_o, tm_pull, x, dw, pw,
                                                                      pixels / kTilePx, kn.mid_from, kn.mid_to, kn.mid_n,
                                                                      kn.park_from, kn);
}
```

```cpp
#include <cuda_runtime.h>
#include <cuda_bf16.h>
#include <cuda.h>
#include <stdint.h>

namespace {

constexpr int kC = 384;
constexpr int kTilePx = 32;
constexpr int kStages = 5;
constexpr int kOutBufs = 8;
constexpr int kPark = 5;
constexpr int kThreads = 512;
constexpr int kStageBytes = kTilePx * kC * 2;
constexpr int kOutBytes = kTilePx * 192 * 2;
constexpr int kWChunkBytes = 64 * 192 * 2;
constexpr int kXSlabBytes = 64 * 128 * 2;
constexpr int kWOff = 3 * kStageBytes;
constexpr int kOutOff = kStages * kStageBytes;
constexpr int kSpillOff = kOutOff + kOutBufs * kOutBytes;
constexpr int kDwOff = kSpillOff;
constexpr int kScratchOff = kSpillOff + 1024;
constexpr int kFullOff = kSpillOff + 384 * 28;
constexpr int kEmptyOff = kFullOff + 8 * kStages;
constexpr int kOFullOff = kEmptyOff + 8 * kStages;
constexpr int kOEmptyOff = kOFullOff + 8 * kOutBufs;
constexpr int kWBarOff = kOEmptyOff + 8 * kOutBufs;
constexpr int kXBarOff = kWBarOff + 8 * 3;
constexpr int kDwBarOff = kXBarOff + 8 * 3;
constexpr int kPullBarOff = kDwBarOff + 8;
constexpr int kSlotOff = kPullBarOff + 8;
constexpr int kOSlotOff = kSlotOff + 4 * kStages;
constexpr int kPSlotOff = kOSlotOff + 4 * kOutBufs;
constexpr int kSmemBytes = kPSlotOff + 4 * (kPark + 1);
static_assert(kWChunkBytes == kStageBytes && kWOff + 6 * kWChunkBytes <= kDwOff, "weight staging");
static_assert(kSmemBytes <= 232448, "shared memory");

constexpr int kGapPts = 6, kHoldPts = 8, kLeadPts = 10;
struct Knobs {
    int first_gap;
    int pull_n, pull_t0, pull_dt;
    int pf_from, pf_t0, pf_dt;
    int static_tiles;
    int mid_from, mid_to, mid_n;
    int park_from;
    int stream_from;
    int slack;
    int gap_pos[kGapPts], gap[kGapPts];
    int hold_pos[kHoldPts], hold[kHoldPts];
    int lead_pos[kLeadPts], lead[kLeadPts];
    int lead_slope[kLeadPts];
};
#define DEFAULT_KNOBS {505, 5, 25, 410, 561, 210, 604, 18, 1601, 3145, 2, 3416, 4355, 280, \
    {0, 400, 1520, 2460, 3430, 3971}, {0, 0, 830, 972, 795, 0}, \
    {0, 456, 575, 957, 2000, 3000, 4278, 4608}, {0, 1, 2, 3, 3, 3, 1, 1}, \
    {0, 835, 1464, 1980, 2077, 2380, 3630, 3798, 3860, 4514}, {322, 370, 542, 320, 340, 324, 121, 218, 259, 173}}
constexpr Knobs g_knobs = DEFAULT_KNOBS;

__device__ unsigned int g_tile_counter;

__device__ __forceinline__ uint32_t smem_u32(const void* p) { return (uint32_t)__cvta_generic_to_shared(p); }

__device__ __forceinline__ void mbar_init(uint32_t bar, uint32_t cnt) {
    asm volatile("mbarrier.init.shared::cta.b64 [%0], %1;" ::"r"(bar), "r"(cnt) : "memory");
}
__device__ __forceinline__ void mbar_expect_tx(uint32_t bar, uint32_t bytes) {
    asm volatile("mbarrier.arrive.expect_tx.shared::cta.b64 _, [%0], %1;" ::"r"(bar), "r"(bytes) : "memory");
}
__device__ __forceinline__ void mbar_arrive(uint32_t bar) {
    asm volatile("mbarrier.arrive.shared::cta.b64 _, [%0];" ::"r"(bar) : "memory");
}
__device__ __forceinline__ void mbar_arrive_cluster(uint32_t bar) {
    asm volatile("mbarrier.arrive.shared::cluster.b64 _, [%0];" ::"r"(bar) : "memory");
}
__device__ __forceinline__ void mbar_wait(uint32_t bar, uint32_t parity) {
    asm volatile(
        "{\n.reg .pred p;\n.reg .u32 n;\n"
        "mbarrier.try_wait.parity.shared::cta.b64 p, [%0], %1;\n"
        "@p bra DONE;\n"
        "mov.u32 n, 0;\n"
        "LOOP:\n"
        "mbarrier.try_wait.parity.shared::cta.b64 p, [%0], %1;\n"
        "@p bra DONE;\n"
        "add.u32 n, n, 1;\n"
        "setp.lt.u32 p, n, 4194304;\n"
        "@p bra LOOP;\n"
        "trap;\n"
        "DONE:\n}" ::"r"(bar), "r"(parity) : "memory");
}
__device__ __forceinline__ uint32_t map_to_cta(uint32_t addr, uint32_t cta) {
    uint32_t r;
    asm("mapa.shared::cluster.u32 %0, %1, %2;" : "=r"(r) : "r"(addr), "r"(cta));
    return r;
}
__device__ __forceinline__ void named_bar_sync(int id, int n) { asm volatile("bar.sync %0, %1;" ::"r"(id), "r"(n) : "memory"); }
__device__ __forceinline__ void named_bar_arrive(int id, int n) { asm volatile("bar.arrive %0, %1;" ::"r"(id), "r"(n) : "memory"); }
__device__ __forceinline__ void cluster_arrive() {
    __syncwarp();
    asm volatile("barrier.cluster.arrive.relaxed.aligned;" ::: "memory");
}
__device__ __forceinline__ void cluster_wait() {
    __syncwarp();
    asm volatile("barrier.cluster.wait.acquire.aligned;" ::: "memory");
}
__device__ __forceinline__ void prefetch_line(const void* p) { asm volatile("prefetch.global.L2 [%0];" ::"l"(p) : "memory"); }
__device__ __forceinline__ void prefetch_map(const CUtensorMap* m) { asm volatile("prefetch.tensormap [%0];" ::"l"(m) : "memory"); }
__device__ __forceinline__ uint32_t globaltimer() {
    uint32_t t;
    asm volatile("mov.u32 %0, %%globaltimer_lo;" : "=r"(t));
    return t;
}
__device__ __forceinline__ uint32_t clock32() {
    uint32_t t;
    asm volatile("mov.u32 %0, %%clock;" : "=r"(t));
    return t;
}
__device__ __forceinline__ int lds32(uint32_t addr) {
    int v;
    asm volatile("ld.shared.b32 %0, [%1];" : "=r"(v) : "r"(addr) : "memory");
    return v;
}
__device__ __forceinline__ int lds32_volatile(uint32_t addr) {
    int v;
    asm volatile("ld.volatile.shared.b32 %0, [%1];" : "=r"(v) : "r"(addr) : "memory");
    return v;
}
__device__ __forceinline__ void sts32(uint32_t addr, int v) { asm volatile("st.shared.b32 [%0], %1;" ::"r"(addr), "r"(v) : "memory"); }

#define ACC4(o) "+f"(d[o]), "+f"(d[o + 1]), "+f"(d[o + 2]), "+f"(d[o + 3])
#define ACC16(o) ACC4(o), ACC4(o + 4), ACC4(o + 8), ACC4(o + 12)
__device__ __forceinline__ void wgmma_rs(float (&d)[32], const uint32_t (&a)[4], uint64_t desc_b, int scale_d) {
    asm volatile(
        "{\n.reg .pred p;\nsetp.ne.b32 p, %37, 0;\n"
        "wgmma.mma_async.sync.aligned.m64n64k16.f32.bf16.bf16 "
        "{%0, %1, %2, %3, %4, %5, %6, %7, %8, %9, %10, %11, %12, %13, %14, %15, "
        "%16, %17, %18, %19, %20, %21, %22, %23, %24, %25, %26, %27, %28, %29, %30, %31}, "
        "{%32, %33, %34, %35}, %36, p, 1, 1, 0;\n}"
        : ACC16(0), ACC16(16)
        : "r"(a[0]), "r"(a[1]), "r"(a[2]), "r"(a[3]), "l"(desc_b), "r"(scale_d));
}
__device__ __forceinline__ void wgmma_rs(float (&d)[16], const uint32_t (&a)[4], uint64_t desc_b, int scale_d) {
    asm volatile(
        "{\n.reg .pred p;\nsetp.ne.b32 p, %21, 0;\n"
        "wgmma.mma_async.sync.aligned.m64n32k16.f32.bf16.bf16 "
        "{%0, %1, %2, %3, %4, %5, %6, %7, %8, %9, %10, %11, %12, %13, %14, %15}, "
        "{%16, %17, %18, %19}, %20, p, 1, 1, 0;\n}"
        : ACC16(0)
        : "r"(a[0]), "r"(a[1]), "r"(a[2]), "r"(a[3]), "l"(desc_b), "r"(scale_d));
}
__device__ __forceinline__ uint64_t make_desc(uint32_t addr, uint32_t group_stride) {
    return (uint64_t(1) << 62) | (uint64_t(group_stride >> 4) << 32) | (uint64_t(1) << 16) | (uint64_t)((addr & 0x3FFFF) >> 4);
}
__device__ __forceinline__ constexpr uint64_t desc_k(int k) { return (uint64_t)(((k >> 2) * 1024 + (k & 3) * 32) >> 4); }

__device__ __forceinline__ uint32_t pack_bf16(float lo, float hi) {
    uint32_t r;
    asm("cvt.rn.bf16x2.f32 %0, %1, %2;" : "=r"(r) : "f"(hi), "f"(lo));
    return r;
}
__device__ __forceinline__ uint32_t mul_bf16x2(uint32_t a, uint32_t b) {
    uint32_t r;
    asm("mul.rn.bf16x2 %0, %1, %2;" : "=r"(r) : "r"(a), "r"(b));
    return r;
}

__global__ void __cluster_dims__(2, 1, 1) __launch_bounds__(kThreads, 1)
dwsep_kernel(const __grid_constant__ CUtensorMap tm_w, const __grid_constant__ CUtensorMap tm_x0,
             const __grid_constant__ CUtensorMap tm_x, const __grid_constant__ CUtensorMap tm_o,
             const __grid_constant__ CUtensorMap tm_pull,
             const __nv_bfloat16* __restrict__ x, const __nv_bfloat16* __restrict__ dw,
             const __nv_bfloat16* __restrict__ pw, int num_tiles,
             int mid_from, int mid_to, int mid_n, int park_from, int static_tiles, int stream_from,
             const __grid_constant__ Knobs kn) {
    extern __shared__ __align__(1024) uint8_t smem_raw[];
    const uint32_t sb = smem_u32(smem_raw);

    uint32_t rank;
    asm("mov.u32 %0, %%cluster_ctarank;" : "=r"(rank));
    const int cluster = blockIdx.x >> 1;
    auto static_tile = [&](int i) { return (i >> 1) * gridDim.x + cluster * 2 + (i & 1); };

    if (threadIdx.x < 32) {
        prefetch_line(threadIdx.x < 18 ? (const char*)pw + (blockIdx.x & 127) * 2304 + threadIdx.x * 128
                                       : (const char*)dw + min(threadIdx.x - 18, 5) * 128);
    } else if (threadIdx.x < 224) {
        const uint32_t c0 = __shfl_sync(0xffffffffu, clock32(), 0), chunk = (threadIdx.x >> 5) - 1;
        const uint32_t delay = ((chunk >> 1) * gridDim.x + blockIdx.x) * kn.first_gap >> 7;
        for (int n = 0; clock32() - c0 < delay && n < 1024; n++) {}
        prefetch_line((const char*)x + (size_t)blockIdx.x * kStageBytes + (threadIdx.x & 31) * 768 + chunk * 128);
    } else if (threadIdx.x == 288) {
        prefetch_map(&tm_w);
        prefetch_map(&tm_x0);
        if (rank == 1) prefetch_map(&tm_pull);
    }
    if (threadIdx.x >> 5 == 8) {
        if (threadIdx.x == 256) {
#pragma unroll
            for (int b = 0; b < 7; b++) mbar_init(sb + kWBarOff + 8 * b, 1);
            asm volatile("fence.proxy.async.shared::cta;" ::: "memory");
        }
        __syncwarp();
        named_bar_arrive(8, 384);
        if (threadIdx.x == 256) {
            mbar_expect_tx(sb + kDwBarOff, kC * 2);
            asm volatile("cp.async.bulk.shared::cluster.global.mbarrier::complete_tx::bytes [%0], [%1], %2, [%3];"
                         ::"r"(sb + kDwOff), "l"(dw), "r"(kC * 2), "r"(sb + kDwBarOff) : "memory");
#pragma unroll
            for (int j = 0; j < 3; j++) {
                mbar_expect_tx(sb + kWBarOff + 8 * j, 2 * kWChunkBytes);
#pragma unroll
                for (int c = 2 * j; c < 2 * j + 2; c++)
                    asm volatile("cp.async.bulk.tensor.3d.shared::cluster.global.mbarrier::complete_tx::bytes [%0], [%1, {%3, %4, %5}], [%2];"
                                 ::"r"(sb + kWOff + c * kWChunkBytes), "l"(&tm_w), "r"(sb + kWBarOff + 8 * j), "r"(0), "r"(c * 64),
                                   "r"((int)rank * 3) : "memory");
                mbar_expect_tx(sb + kXBarOff + 8 * j, kXSlabBytes);
                asm volatile("cp.async.bulk.tensor.4d.shared::cluster.global.mbarrier::complete_tx::bytes [%0], [%1, {%3, %3, %4, %5}], [%2];"
                             ::"r"(sb + j * kXSlabBytes), "l"(&tm_x0), "r"(sb + kXBarOff + 8 * j), "r"(0), "r"(2 * j),
                               "r"(cluster * 8) : "memory");
            }
        }
        __syncwarp();
    }

    if (threadIdx.x < 384) {
        asm volatile("setmaxnreg.inc.sync.aligned.u32 160;");
        cluster_arrive();
        if (threadIdx.x >> 5 != 8) named_bar_sync(8, 384);
        const int wg = __shfl_sync(0xffffffffu, threadIdx.x >> 7, 0);
        const int warp = (threadIdx.x >> 5) & 3;
        const int lane = threadIdx.x & 31;
        const int mi = lane >> 3, ri = lane & 7;
        const uint32_t leader_empty = map_to_cta(sb + kEmptyOff, 0);
        uint32_t st_off = sb + kOutOff + (((mi >> 1) * 8 + ri) * 3 + wg) * 128 + (((2 * warp + (mi & 1)) ^ ((3 * ri + wg) & 7)) << 4);
        int s = 0, ob = 0;
        uint32_t ph = 0, oph = 1;
        auto release_stage = [&]() {
            if (lane == 0) mbar_arrive_cluster(leader_empty + 8 * s);
            if (++s == kStages) { s = 0; ph ^= 1; }
        };
        auto pack = [&](uint32_t (&p)[8], const float* acc) {
#pragma unroll
            for (int k = 0; k < 8; k++) p[k] = pack_bf16(acc[2 * k], acc[2 * k + 1]);
        };
        auto put = [&](const uint32_t (&p)[8], int t) {
            mbar_wait(sb + kOEmptyOff + 8 * ob, oph);
            if (threadIdx.x == 0) sts32(sb + kOSlotOff + 4 * ob, t);
#pragma unroll
            for (int q = 0; q < 2; q++)
                asm volatile("stmatrix.sync.aligned.m8n8.x4.trans.shared.b16 [%0], {%1, %2, %3, %4};"
                             ::"r"(st_off + ob * kOutBytes + q * (16 * 384)), "r"(p[4 * q]), "r"(p[4 * q + 1]),
                               "r"(p[4 * q + 2]), "r"(p[4 * q + 3]) : "memory");
            asm volatile("fence.proxy.async.shared::cta;" ::: "memory");
            __syncwarp();
            if (lane == 0) mbar_arrive(sb + kOFullOff + 8 * ob);
            if (++ob == kOutBufs) { ob = 0; oph ^= 1; }
        };
        auto my_turn = [&]() { named_bar_sync(2 + wg, 256); };
        auto pass_turn = [&]() { named_bar_arrive(wg == 2 ? 2 : 3 + wg, 256); };
        if (wg == 2) pass_turn();

        uint32_t a[24][4];
        {
            float acc0[32];
            uint32_t dws[48];
            mbar_wait(sb + kDwBarOff, 0);
#pragma unroll
            for (int k = 0; k < 48; k++) dws[k] = lds32(sb + kDwOff + k * 16 + (lane & 3) * 4);
            cluster_wait();
            if (lane < 3) mbar_arrive_cluster(leader_empty + 8 * lane);
            const uint32_t wbase = sb + kWOff + wg * 8192 + ((mi >> 1) * 8 + ri) * 128 + (((2 * warp + (mi & 1)) ^ ri) << 4);
            const uint64_t desc = make_desc(sb, 2048);
#pragma unroll
            for (int j = 0; j < 3; j++) {
                mbar_wait(sb + kWBarOff + 8 * j, 0);
#pragma unroll
                for (int k = 8 * j; k < 8 * j + 8; k++) {
                    asm volatile("ldmatrix.sync.aligned.m8n8.x4.trans.shared.b16 {%0, %1, %2, %3}, [%4];"
                                 : "=r"(a[k][0]), "=r"(a[k][1]), "=r"(a[k][2]), "=r"(a[k][3])
                                 : "r"(wbase + (k >> 2) * kWChunkBytes + (k & 3) * 2048) : "memory");
                    a[k][0] = mul_bf16x2(a[k][0], dws[2 * k]);
                    a[k][1] = mul_bf16x2(a[k][1], dws[2 * k]);
                    a[k][2] = mul_bf16x2(a[k][2], dws[2 * k + 1]);
                    a[k][3] = mul_bf16x2(a[k][3], dws[2 * k + 1]);
                }
                uint32_t dep = 0;
#pragma unroll
                for (int k = 8 * j; k < 8 * j + 8; k++) dep ^= a[k][3];
                dep &= num_tiles >> 24;
                if (j == 0 && lane >= 3 && lane < kStages) mbar_arrive_cluster(leader_empty + 8 * lane + dep);
                if (j == 2) {
                    named_bar_arrive((wg == 0 ? 6 : 5) + dep, 384);
                    named_bar_arrive(wg == 2 ? 6 : 7, 384);
                }
                mbar_wait(sb + kXBarOff + 8 * j, 0);
                my_turn();
                asm volatile("wgmma.fence.sync.aligned;" ::: "memory");
#pragma unroll
                for (int k = 0; k < 8; k++) wgmma_rs(acc0, a[8 * j + k], desc + (j * kXSlabBytes >> 4) + desc_k(k), j + k != 0);
                pass_turn();
            }
            asm volatile("wgmma.commit_group.sync.aligned;" ::: "memory");
            named_bar_sync(5 + wg, 384);
            asm volatile("wgmma.wait_group.sync.aligned 0;" ::: "memory");
            release_stage();
            release_stage();
            uint32_t p[8];
            pack(p, acc0);
            put(p, static_tile(0));
            pack(p, acc0 + 16);
            put(p, static_tile(1));
        }

        float acc[16];
        uint32_t park[kPark][8], park_last;
        int parked = 0;
        st_off += num_tiles >> 24;
        auto spill_addr = [&](int base, int shift, int zero) {
            return ((st_off + zero) >> shift) + (sb - (sb >> shift) + kSpillOff + base - (kOutOff >> shift));
        };
        asm volatile("mov.b32 %0, 0;" : "=r"(park_last));
#pragma unroll
        for (int k = 0; k < kPark * 8; k++) asm volatile("mov.b32 %0, 0;" : "=r"(park[k / 8][k % 8]));
#pragma unroll 1
        while (true) {
            mbar_wait(sb + kFullOff + 8 * s, ph);
            const int t = lds32(sb + kSlotOff + 4 * s);
            if (t >= num_tiles) break;
            const uint64_t desc = make_desc(sb + s * kStageBytes, 6144);
            my_turn();
            asm volatile("wgmma.fence.sync.aligned;" ::: "memory");
#pragma unroll
            for (int k = 0; k < 24; k++) {
                if (k == 19) pass_turn();
                wgmma_rs(acc, a[k], desc + desc_k(k), k != 0);
            }
            asm volatile("wgmma.commit_group.sync.aligned;" ::: "memory");
            asm volatile("wgmma.wait_group.sync.aligned 0;" ::: "memory");
            release_stage();
            const int keep = t >= park_from ? kPark + 1 : t >= mid_from && t < mid_to ? mid_n : 0;
            if (parked < keep) {
#pragma unroll
                for (int k = 0; k < kPark; k++)
                    if (parked == k) pack(park[k], acc);
                if (parked == kPark) {
                    uint32_t p[8];
                    pack(p, acc);
                    mbar_wait(sb + kPullBarOff, 0);
                    asm volatile("st.shared.v4.b32 [%0], {%1, %2, %3, %4};"
                                 ::"r"(spill_addr(0, 0, 0)), "r"(p[0]), "r"(p[1]), "r"(p[2]), "r"(p[3]) : "memory");
                    asm volatile("st.shared.v2.b32 [%0], {%1, %2};" ::"r"(spill_addr(6144, 1, t >> 24)), "r"(p[4]), "r"(p[5]) : "memory");
                    sts32(spill_addr(9216, 2, t >> 24), p[6]);
                    asm volatile("xor.b32 %0, %1, %2;" : "=r"(park_last) : "r"(p[7]), "r"(st_off));
                }
                if (threadIdx.x == 0) sts32(sb + kPSlotOff + 4 * parked, t);
                parked++;
            } else {
                uint32_t p[8];
                pack(p, acc);
                put(p, t);
                if (parked > keep) {
#pragma unroll
                    for (int k = 2; k >= 0; k--)
                        if (k < parked) put(park[k], threadIdx.x == 0 ? lds32(sb + kPSlotOff + 4 * k) : 0);
                    parked = 0;
                }
            }
        }
#pragma unroll
        for (int k = 0; k < kPark; k++)
            if (k < parked) put(park[k], threadIdx.x == 0 ? lds32(sb + kPSlotOff + 4 * k) : 0);
        if (parked > kPark) {
            uint32_t p[8];
            asm volatile("ld.shared.v4.b32 {%0, %1, %2, %3}, [%4];"
                         : "=r"(p[0]), "=r"(p[1]), "=r"(p[2]), "=r"(p[3]) : "r"(spill_addr(0, 0, 0)) : "memory");
            asm volatile("ld.shared.v2.b32 {%0, %1}, [%2];" : "=r"(p[4]), "=r"(p[5]) : "r"(spill_addr(6144, 1, parked >> 24)) : "memory");
            p[6] = lds32(spill_addr(9216, 2, parked >> 24));
            asm volatile("xor.b32 %0, %1, %2;" : "=r"(p[7]) : "r"(park_last), "r"(st_off));
            put(p, threadIdx.x == 0 ? lds32(sb + kPSlotOff + 4 * kPark) : 0);
        }
        mbar_wait(sb + kPullBarOff, 0);
#pragma unroll 1
        for (int k = 0; k < 2; k++) {
            mbar_wait(sb + kOEmptyOff + 8 * ob, oph);
            if (threadIdx.x == 0) sts32(sb + kOSlotOff + 4 * ob, num_tiles);
            if (lane == 0) mbar_arrive(sb + kOFullOff + 8 * ob);
            if (++ob == kOutBufs) { ob = 0; oph ^= 1; }
        }
    } else {
        asm volatile("setmaxnreg.dec.sync.aligned.u32 32;");
        const int role = __shfl_sync(0xffffffffu, (threadIdx.x >> 5) & 3, 0);
        const bool lead = (threadIdx.x & 31) == 0;
        if (role >= 2) {
            const int par = role & 1;
            if (lead) {
                if (par == 0) {
#pragma unroll
                    for (int b = 0; b < kOutBufs; b++) {
                        mbar_init(sb + kOFullOff + 8 * b, 12);
                        mbar_init(sb + kOEmptyOff + 8 * b, 1);
                    }
                } else {
#pragma unroll
                    for (int s = 0; s < kStages; s++) {
                        mbar_init(sb + kFullOff + 8 * s, 1);
                        mbar_init(sb + kEmptyOff + 8 * s, 24);
                        if (s < 2) mbar_arrive(sb + kFullOff + 8 * s);
                    }
                    prefetch_map(&tm_x);
                    prefetch_map(&tm_o);
                }
                asm volatile("fence.mbarrier_init.release.cluster;" ::: "memory");
            }
            cluster_arrive();
            cluster_wait();
            uint64_t normal, streaming;
            asm volatile("createpolicy.fractional.L2::evict_normal.b64 %0, 1.0;" : "=l"(normal));
            asm volatile("createpolicy.fractional.L2::evict_first.b64 %0, 1.0;" : "=l"(streaming));
            int head = par, tail = par, held = 0, pos = 0, k = 0, hold = 0, next = 0;
            uint32_t ph = 0;
            auto issue = [&](int u) {
                if (lead) {
                    asm volatile("cp.async.bulk.tensor.3d.global.shared::cta.bulk_group.L2::cache_hint [%0, {%2, %3, %4}], [%1], %5;"
                                 ::"l"(&tm_o), "r"(sb + kOutOff + tail * kOutBytes), "r"(0), "r"((int)rank * 3),
                                   "r"(u * kTilePx), "l"(pos >= stream_from ? streaming : normal) : "memory");
                    asm volatile("cp.async.bulk.commit_group;" ::: "memory");
                }
                if ((tail += 2) >= kOutBufs) tail = par;
                held--;
            };
#pragma unroll 1
            while (true) {
                const bool push = held > 0 && held >= hold;
                const int oldest = __shfl_sync(0xffffffffu, lds32(sb + kOSlotOff + 4 * tail), 0);
                int freed = tail, n = push;
                mbar_wait(sb + kOFullOff + 8 * head, ph);
                if (push) issue(oldest);
                const int t = __shfl_sync(0xffffffffu, lds32(sb + kOSlotOff + 4 * head), 0);
                if (t < num_tiles) {
                    held++;
                    pos = max(pos, t);
                    if ((head += 2) >= kOutBufs) { head = par; ph ^= 1; }
#pragma unroll 1
                    while (pos >= next) {
                        hold = kn.hold[k++];
                        next = k < kHoldPts ? kn.hold_pos[k] : 0x7fffffff;
                    }
                } else {
                    hold = 0;
                }
#pragma unroll 1
                for (; held > hold; n++) issue(lds32(sb + kOSlotOff + 4 * tail));
#pragma unroll 1
                for (; n > 1; n--) {
                    if (lead) {
                        if (n == 2) asm volatile("cp.async.bulk.wait_group.read 1;" ::: "memory");
                        else asm volatile("cp.async.bulk.wait_group.read 2;" ::: "memory");
                        mbar_arrive(sb + kOEmptyOff + 8 * freed);
                    }
                    if ((freed += 2) >= kOutBufs) freed = par;
                }
                if (n && lead) {
                    asm volatile("cp.async.bulk.wait_group.read 0;" ::: "memory");
                    mbar_arrive(sb + kOEmptyOff + 8 * freed);
                }
                if (t >= num_tiles) break;
            }
        } else if (role == 1) {
            const uint32_t t_start = __shfl_sync(0xffffffffu, globaltimer(), 0);
            const uint32_t my_slot = sb + kSlotOff + 4 * min(threadIdx.x & 31, kStages - 1);
            sts32(my_slot, 0);
            __threadfence_block();
            cluster_arrive();
            int k = 0;
#pragma unroll 1
            for (int t = blockIdx.x + gridDim.x; t < num_tiles; t += gridDim.x) {
                if (t < kn.pf_from) continue;
                const uint32_t due = kn.pf_t0 + (t - gridDim.x) * kn.pf_dt / gridDim.x;
                for (int n = 0; globaltimer() - t_start < due && n < 4096; n++) __nanosleep(50);
#pragma unroll 1
                while (k + 1 < kLeadPts && t >= kn.lead_pos[k + 1]) k++;
                const int max_lead = kn.lead[k] + ((t - kn.lead_pos[k]) * kn.lead_slope[k] >> 16);
                for (int n = 0; t > max_lead && n < 4096; n++) {
                    const int front = __reduce_max_sync(0xffffffffu, lds32_volatile(my_slot));
                    if (t - max_lead <= front || front >= num_tiles) break;
                    __nanosleep(50);
                }
                if (lead)
                    asm volatile("cp.async.bulk.prefetch.L2.global [%0], %1;"
                                 ::"l"((const char*)x + (size_t)t * kStageBytes), "r"(kStageBytes) : "memory");
            }
            cluster_wait();
        } else {
            const uint32_t t_start = __shfl_sync(0xffffffffu, globaltimer(), 0);
            if (lead) {
                mbar_init(sb + kPullBarOff, 1);
                asm volatile("fence.proxy.async.shared::cta;" ::: "memory");
                mbar_expect_tx(sb + kPullBarOff, rank * 3072 * kn.pull_n);
            }
            __threadfence_block();
            cluster_arrive();
            if (__shfl_sync(0xffffffffu, rank, 0) == 1) {
#pragma unroll 1
                for (int i = 0; i < kn.pull_n; i++) {
                    const uint32_t due = kn.pull_t0 + (i * gridDim.x + blockIdx.x) * kn.pull_dt / gridDim.x;
                    for (int n = 0; globaltimer() - t_start < due && n < 4096; n++) {}
                    if (lead)
                        asm volatile("cp.async.bulk.tensor.2d.shared::cluster.global.mbarrier::complete_tx::bytes [%0], [%1, {%3, %4}], [%2];"
                                     ::"r"(sb + kScratchOff), "l"(&tm_pull), "r"(sb + kPullBarOff), "r"(0),
                                       "r"(static_tile(i + 2) * 192) : "memory");
                }
            }
            cluster_wait();
            if (__shfl_sync(0xffffffffu, rank, 0) == 0) {
                const uint32_t peer = map_to_cta(sb, 1);
                const int nstatic = static_tiles * (gridDim.x >> 1);
                const unsigned last_fetch = num_tiles - nstatic + gridDim.x - 1;
                mbar_wait(sb + kEmptyOff, 0);
                mbar_wait(sb + kEmptyOff + 8, 0);
                int s = 2, g = 0, gap = 0, gap_next = 0;
                uint32_t earliest = 0;
                uint32_t ph = 0;
                auto fetch = [&](unsigned& raw) {
                    if (lead) asm volatile("atom.global.inc.u32 %0, [%1], %2;" : "=r"(raw) : "l"(&g_tile_counter), "r"(last_fetch) : "memory");
                };
                auto load = [&](int t, bool valid) {
                    mbar_wait(sb + kEmptyOff + 8 * s, ph);
                    __syncwarp();
                    if (gap) {
                        uint32_t now = globaltimer() - t_start;
                        for (int n = 0; now < earliest && n < 4096; n++) now = globaltimer() - t_start;
                        earliest = max(earliest, now - kn.slack) + gap;
                    }
                    const uint32_t full = kFullOff + 8 * s, slot = kSlotOff + 4 * s;
                    const uint32_t bytes = valid ? kStageBytes : 0;
                    if (lead && valid)
                        asm volatile(
                            "cp.async.bulk.tensor.4d.shared::cluster.global.mbarrier::complete_tx::bytes.multicast::cluster "
                            "[%0], [%1, {%3, %3, %3, %4}], [%2], %5;"
                            ::"r"(sb + s * kStageBytes), "l"(&tm_x), "r"(sb + full), "r"(0), "r"(t * (kTilePx / 8)),
                              "h"((uint16_t)3) : "memory");
                    if (lead) {
                        sts32(sb + slot, t);
                        mbar_expect_tx(sb + full, bytes);
                        asm volatile("mbarrier.arrive.expect_tx.shared::cluster.b64 _, [%0], %1;" ::"r"(peer + full), "r"(bytes + 4) : "memory");
                        asm volatile("st.async.weak.shared::cluster.mbarrier::complete_tx::bytes.b32 [%0], %1, [%2];"
                                     ::"r"(peer + slot), "r"(t), "r"(peer + full) : "memory");
                    }
                    if (++s == kStages) { s = 0; ph ^= 1; }
#pragma unroll 1
                    while (t >= gap_next) {
                        gap = kn.gap[g++];
                        gap_next = g < kGapPts ? kn.gap_pos[g] : 0x7fffffff;
                    }
                };
                unsigned raw0 = 0, raw1 = 0;
#pragma unroll 1
                for (int i = 2; i < static_tiles; i++) {
                    if (i == static_tiles - 2) fetch(raw0);
                    if (i == static_tiles - 1) fetch(raw1);
                    load(static_tile(i), true);
                }
                auto step = [&](unsigned& raw) -> bool {
                    const int t = nstatic + __shfl_sync(0xffffffffu, raw, 0);
                    const bool valid = t < num_tiles;
                    if (valid) fetch(raw);
                    load(t, valid);
                    return valid;
                };
#pragma unroll 1
                while (step(raw0) && step(raw1)) {}
#pragma unroll 1
                for (int k = 1; k < kStages; k++) {
                    mbar_wait(sb + kEmptyOff + 8 * s, ph);
                    if (++s == kStages) { s = 0; ph ^= 1; }
                }
            }
        }
    }
}

typedef CUresult (*EncodeTiledFn)(CUtensorMap*, CUtensorMapDataType, cuuint32_t, void*, const cuuint64_t*,
                                  const cuuint64_t*, const cuuint32_t*, const cuuint32_t*, CUtensorMapInterleave,
                                  CUtensorMapSwizzle, CUtensorMapL2promotion, CUtensorMapFloatOOBfill);

}

extern "C" void kernel_launch(void* const* d_in, const int* in_sizes, int n_in, void* d_out, int out_size) {
    (void)n_in; (void)out_size;
    const __nv_bfloat16* x = (const __nv_bfloat16*)d_in[0];
    const __nv_bfloat16* dw = (const __nv_bfloat16*)d_in[1];
    const __nv_bfloat16* pw = (const __nv_bfloat16*)d_in[2];
    const int pixels = in_sizes[0] / kC;

    static EncodeTiledFn encode = nullptr;
    static int grid = 0;
    if (!encode) {
        void* fn = nullptr;
        cudaDriverEntryPointQueryResult qr;
        cudaGetDriverEntryPoint("cuTensorMapEncodeTiled", &fn, cudaEnableDefault, &qr);
        encode = (EncodeTiledFn)fn;
        cudaFuncSetAttribute(dwsep_kernel, cudaFuncAttributeMaxDynamicSharedMemorySize, kSmemBytes);
        int sms = 0, clusters = 0;
        cudaDeviceGetAttribute(&sms, cudaDevAttrMultiProcessorCount, 0);
        cudaLaunchConfig_t cfg = {};
        cudaLaunchAttribute attr = {};
        attr.id = cudaLaunchAttributeClusterDimension;
        attr.val.clusterDim.x = 2;
        attr.val.clusterDim.y = attr.val.clusterDim.z = 1;
        cfg.gridDim = dim3(sms & ~1);
        cfg.blockDim = dim3(kThreads);
        cfg.dynamicSmemBytes = kSmemBytes;
        cfg.attrs = &attr;
        cfg.numAttrs = 1;
        if (cudaOccupancyMaxActiveClusters(&clusters, dwsep_kernel, &cfg) != cudaSuccess || clusters < 1) {
            (void)cudaGetLastError();
            clusters = sms / 2;
        }
        grid = 2 * (clusters < sms / 2 ? clusters : sms / 2);
    }

    CUtensorMap tm_w, tm_x0, tm_x, tm_o, tm_pull;
    auto make_map = [&](CUtensorMap* m, const void* base, int rank, const cuuint64_t* dims, const cuuint64_t* strides,
                        const cuuint32_t* box, CUtensorMapL2promotion promo) {
        const cuuint32_t ones[4] = {1, 1, 1, 1};
        encode(m, CU_TENSOR_MAP_DATA_TYPE_BFLOAT16, rank, (void*)base, dims, strides, box, ones,
               CU_TENSOR_MAP_INTERLEAVE_NONE, CU_TENSOR_MAP_SWIZZLE_128B, promo, CU_TENSOR_MAP_FLOAT_OOB_FILL_NONE);
    };
    {
        const cuuint64_t dims[3] = {64, kC, 6}, strides[2] = {kC * 2, 128};
        const cuuint32_t box[3] = {64, 64, 3};
        make_map(&tm_w, pw, 3, dims, strides, box, CU_TENSOR_MAP_L2_PROMOTION_L2_128B);
    }
    {
        const cuuint64_t dims[4] = {64, 8, 6, (cuuint64_t)pixels / 8}, strides[3] = {kC * 2, 128, kC * 2 * 8};
        const cuuint32_t box0[4] = {64, 8, 2, 8}, box[4] = {64, 8, 6, kTilePx / 8};
        make_map(&tm_x0, x, 4, dims, strides, box0, CU_TENSOR_MAP_L2_PROMOTION_L2_128B);
        make_map(&tm_x, x, 4, dims, strides, box, CU_TENSOR_MAP_L2_PROMOTION_L2_128B);
    }
    {
        const cuuint64_t dims[3] = {64, 6, (cuuint64_t)pixels}, strides[2] = {128, kC * 2};
        const cuuint32_t box[3] = {64, 3, kTilePx};
        make_map(&tm_o, d_out, 3, dims, strides, box, CU_TENSOR_MAP_L2_PROMOTION_NONE);
    }
    {
        const cuuint64_t dims[2] = {64, (cuuint64_t)pixels * 6}, strides[1] = {128};
        const cuuint32_t box[2] = {8, 192}, ones[2] = {1, 1};
        encode(&tm_pull, CU_TENSOR_MAP_DATA_TYPE_BFLOAT16, 2, (void*)x, dims, strides, box, ones, CU_TENSOR_MAP_INTERLEAVE_NONE,
               CU_TENSOR_MAP_SWIZZLE_NONE, CU_TENSOR_MAP_L2_PROMOTION_L2_128B, CU_TENSOR_MAP_FLOAT_OOB_FILL_NONE);
    }
    Knobs kn = g_knobs;
    for (int k = 0; k < kLeadPts; k++)
        kn.lead_slope[k] = k < kLeadPts - 1 ? (kn.lead[k + 1] - kn.lead[k]) * 65536 / (kn.lead_pos[k + 1] - kn.lead_pos[k]) : 0;
    dwsep_kernel<<<grid, kThreads, kSmemBytes, cudaStreamPerThread>>>(tm_w, tm_x0, tm_x, tm_o, tm_pull, x, dw, pw,
                                                                      pixels / kTilePx, kn.mid_from, kn.mid_to, kn.mid_n,
                                                                      kn.park_from, kn.static_tiles, kn.stream_from, kn);
}
```

```cpp
#include <cuda_runtime.h>
#include <cuda_bf16.h>
#include <cuda.h>
#include <stdint.h>

namespace {

constexpr int kC = 384;
constexpr int kTilePx = 32;
constexpr int kStages = 5;
constexpr int kOutBufs = 8;
constexpr int kPark = 5;
constexpr int kThreads = 512;
constexpr int kStageBytes = kTilePx * kC * 2;
constexpr int kOutBytes = kTilePx * 192 * 2;
constexpr int kWChunkBytes = 64 * 192 * 2;
constexpr int kXSlabBytes = 64 * 128 * 2;
constexpr int kWOff = 3 * kStageBytes;
constexpr int kOutOff = kStages * kStageBytes;
constexpr int kSpillOff = kOutOff + kOutBufs * kOutBytes;
constexpr int kDwOff = kSpillOff;
constexpr int kScratchOff = kSpillOff + 1024;
constexpr int kFullOff = kSpillOff + 384 * 28;
constexpr int kEmptyOff = kFullOff + 8 * kStages;
constexpr int kOFullOff = kEmptyOff + 8 * kStages;
constexpr int kOEmptyOff = kOFullOff + 8 * kOutBufs;
constexpr int kWBarOff = kOEmptyOff + 8 * kOutBufs;
constexpr int kXBarOff = kWBarOff + 8 * 3;
constexpr int kDwBarOff = kXBarOff + 8 * 3;
constexpr int kPullBarOff = kDwBarOff + 8;
constexpr int kSlotOff = kPullBarOff + 8;
constexpr int kOSlotOff = kSlotOff + 4 * kStages;
constexpr int kPSlotOff = kOSlotOff + 4 * kOutBufs;
constexpr int kSmemBytes = kPSlotOff + 4 * (kPark + 1);
static_assert(kWChunkBytes == kStageBytes && kWOff + 6 * kWChunkBytes <= kDwOff, "weight staging");
static_assert(kSmemBytes <= 232448, "shared memory");

constexpr int kGapPts = 6, kHoldPts = 12, kLeadPts = 10;
struct Knobs {
    int first_gap;
    int pull_n, pull_t0, pull_dt;
    int pf_from, pf_t0, pf_dt;
    int static_tiles;
    int mid_from, mid_to, mid_n;
    int park_from;
    int stream_from;
    int lag;
    int slack;
    int gap_pos[kGapPts], gap[kGapPts];
    int hold_pos[kHoldPts], hold[kHoldPts];
    int lead_pos[kLeadPts], lead[kLeadPts];
    int lead_slope[kLeadPts];
};
#define DEFAULT_KNOBS {518, 5, 37, 412, 594, 233, 650, 20, 1590, 3275, 2, 3412, 4275, 2, 260, \
    {0, 300, 1810, 2585, 3288, 3946}, {0, 0, 850, 976, 798, 0}, \
    {0, 440, 456, 594, 594, 956, 956, 1910, 3000, 4245, 4382, 4608}, {0, 1, 2, 3, 4, 5, 6, 7, 7, 4, 2, 2}, \
    {0, 833, 1450, 1990, 2100, 2313, 3630, 3800, 3866, 4514}, {227, 371, 540, 332, 388, 329, 132, 209, 234, 152}}
constexpr Knobs g_knobs = DEFAULT_KNOBS;

__device__ unsigned int g_tile_counter;

__device__ __forceinline__ uint32_t smem_u32(const void* p) { return (uint32_t)__cvta_generic_to_shared(p); }

__device__ __forceinline__ void mbar_init(uint32_t bar, uint32_t cnt) {
    asm volatile("mbarrier.init.shared::cta.b64 [%0], %1;" ::"r"(bar), "r"(cnt) : "memory");
}
__device__ __forceinline__ void mbar_expect_tx(uint32_t bar, uint32_t bytes) {
    asm volatile("mbarrier.arrive.expect_tx.shared::cta.b64 _, [%0], %1;" ::"r"(bar), "r"(bytes) : "memory");
}
__device__ __forceinline__ void mbar_arrive(uint32_t bar) {
    asm volatile("mbarrier.arrive.shared::cta.b64 _, [%0];" ::"r"(bar) : "memory");
}
__device__ __forceinline__ void mbar_arrive_cluster(uint32_t bar) {
    asm volatile("mbarrier.arrive.shared::cluster.b64 _, [%0];" ::"r"(bar) : "memory");
}
__device__ __forceinline__ void mbar_wait(uint32_t bar, uint32_t parity) {
    asm volatile(
        "{\n.reg .pred p;\n.reg .u32 n;\n"
        "mbarrier.try_wait.parity.shared::cta.b64 p, [%0], %1;\n"
        "@p bra DONE;\n"
        "mov.u32 n, 0;\n"
        "LOOP:\n"
        "mbarrier.try_wait.parity.shared::cta.b64 p, [%0], %1;\n"
        "@p bra DONE;\n"
        "add.u32 n, n, 1;\n"
        "setp.lt.u32 p, n, 4194304;\n"
        "@p bra LOOP;\n"
        "trap;\n"
        "DONE:\n}" ::"r"(bar), "r"(parity) : "memory");
}
__device__ __forceinline__ uint32_t map_to_cta(uint32_t addr, uint32_t cta) {
    uint32_t r;
    asm("mapa.shared::cluster.u32 %0, %1, %2;" : "=r"(r) : "r"(addr), "r"(cta));
    return r;
}
__device__ __forceinline__ void named_bar_sync(int id, int n) { asm volatile("bar.sync %0, %1;" ::"r"(id), "r"(n) : "memory"); }
__device__ __forceinline__ void named_bar_arrive(int id, int n) { asm volatile("bar.arrive %0, %1;" ::"r"(id), "r"(n) : "memory"); }
__device__ __forceinline__ void cluster_arrive() {
    __syncwarp();
    asm volatile("barrier.cluster.arrive.relaxed.aligned;" ::: "memory");
}
__device__ __forceinline__ void cluster_wait() {
    __syncwarp();
    asm volatile("barrier.cluster.wait.acquire.aligned;" ::: "memory");
}
__device__ __forceinline__ void prefetch_line(const void* p) { asm volatile("prefetch.global.L2 [%0];" ::"l"(p) : "memory"); }
__device__ __forceinline__ void prefetch_map(const CUtensorMap* m) { asm volatile("prefetch.tensormap [%0];" ::"l"(m) : "memory"); }
__device__ __forceinline__ uint32_t globaltimer() {
    uint32_t t;
    asm volatile("mov.u32 %0, %%globaltimer_lo;" : "=r"(t));
    return t;
}
__device__ __forceinline__ uint32_t clock32() {
    uint32_t t;
    asm volatile("mov.u32 %0, %%clock;" : "=r"(t));
    return t;
}
__device__ __forceinline__ int lds32(uint32_t addr) {
    int v;
    asm volatile("ld.shared.b32 %0, [%1];" : "=r"(v) : "r"(addr) : "memory");
    return v;
}
__device__ __forceinline__ int lds32_volatile(uint32_t addr) {
    int v;
    asm volatile("ld.volatile.shared.b32 %0, [%1];" : "=r"(v) : "r"(addr) : "memory");
    return v;
}
__device__ __forceinline__ void sts32(uint32_t addr, int v) { asm volatile("st.shared.b32 [%0], %1;" ::"r"(addr), "r"(v) : "memory"); }

#define ACC4(o) "+f"(d[o]), "+f"(d[o + 1]), "+f"(d[o + 2]), "+f"(d[o + 3])
#define ACC16(o) ACC4(o), ACC4(o + 4), ACC4(o + 8), ACC4(o + 12)
__device__ __forceinline__ void wgmma_rs(float (&d)[32], const uint32_t (&a)[4], uint64_t desc_b, int scale_d) {
    asm volatile(
        "{\n.reg .pred p;\nsetp.ne.b32 p, %37, 0;\n"
        "wgmma.mma_async.sync.aligned.m64n64k16.f32.bf16.bf16 "
        "{%0, %1, %2, %3, %4, %5, %6, %7, %8, %9, %10, %11, %12, %13, %14, %15, "
        "%16, %17, %18, %19, %20, %21, %22, %23, %24, %25, %26, %27, %28, %29, %30, %31}, "
        "{%32, %33, %34, %35}, %36, p, 1, 1, 0;\n}"
        : ACC16(0), ACC16(16)
        : "r"(a[0]), "r"(a[1]), "r"(a[2]), "r"(a[3]), "l"(desc_b), "r"(scale_d));
}
__device__ __forceinline__ void wgmma_rs(float (&d)[16], const uint32_t (&a)[4], uint64_t desc_b, int scale_d) {
    asm volatile(
        "{\n.reg .pred p;\nsetp.ne.b32 p, %21, 0;\n"
        "wgmma.mma_async.sync.aligned.m64n32k16.f32.bf16.bf16 "
        "{%0, %1, %2, %3, %4, %5, %6, %7, %8, %9, %10, %11, %12, %13, %14, %15}, "
        "{%16, %17, %18, %19}, %20, p, 1, 1, 0;\n}"
        : ACC16(0)
        : "r"(a[0]), "r"(a[1]), "r"(a[2]), "r"(a[3]), "l"(desc_b), "r"(scale_d));
}
__device__ __forceinline__ uint64_t make_desc(uint32_t addr, uint32_t group_stride) {
    return (uint64_t(1) << 62) | (uint64_t(group_stride >> 4) << 32) | (uint64_t(1) << 16) | (uint64_t)((addr & 0x3FFFF) >> 4);
}
__device__ __forceinline__ constexpr uint64_t desc_k(int k) { return (uint64_t)(((k >> 2) * 1024 + (k & 3) * 32) >> 4); }

__device__ __forceinline__ uint32_t pack_bf16(float lo, float hi) {
    uint32_t r;
    asm("cvt.rn.bf16x2.f32 %0, %1, %2;" : "=r"(r) : "f"(hi), "f"(lo));
    return r;
}
__device__ __forceinline__ uint32_t mul_bf16x2(uint32_t a, uint32_t b) {
    uint32_t r;
    asm("mul.rn.bf16x2 %0, %1, %2;" : "=r"(r) : "r"(a), "r"(b));
    return r;
}

__global__ void __cluster_dims__(2, 1, 1) __launch_bounds__(kThreads, 1)
dwsep_kernel(const __grid_constant__ CUtensorMap tm_w, const __grid_constant__ CUtensorMap tm_x0,
             const __grid_constant__ CUtensorMap tm_x, const __grid_constant__ CUtensorMap tm_o,
             const __grid_constant__ CUtensorMap tm_pull,
             const __nv_bfloat16* __restrict__ x, const __nv_bfloat16* __restrict__ dw,
             const __nv_bfloat16* __restrict__ pw, int num_tiles,
             int mid_from, int mid_to, int mid_n, int park_from, int static_tiles, int stream_from,
             const __grid_constant__ Knobs kn) {
    extern __shared__ __align__(1024) uint8_t smem_raw[];
    const uint32_t sb = smem_u32(smem_raw);

    uint32_t rank;
    asm("mov.u32 %0, %%cluster_ctarank;" : "=r"(rank));
    const int cluster = blockIdx.x >> 1;
    auto static_tile = [&](int i) { return (i >> 1) * gridDim.x + cluster * 2 + (i & 1); };

    if (threadIdx.x < 32) {
        prefetch_line(threadIdx.x < 18 ? (const char*)pw + (blockIdx.x & 127) * 2304 + threadIdx.x * 128
                                       : (const char*)dw + min(threadIdx.x - 18, 5) * 128);
    } else if (threadIdx.x < 224) {
        const uint32_t c0 = __shfl_sync(0xffffffffu, clock32(), 0), chunk = (threadIdx.x >> 5) - 1;
        const uint32_t delay = ((chunk >> 1) * gridDim.x + blockIdx.x) * kn.first_gap >> 7;
        for (int n = 0; clock32() - c0 < delay && n < 1024; n++) {}
        prefetch_line((const char*)x + (size_t)blockIdx.x * kStageBytes + (threadIdx.x & 31) * 768 + chunk * 128);
    } else if (threadIdx.x == 288) {
        prefetch_map(&tm_w);
        prefetch_map(&tm_x0);
        if (rank == 1) prefetch_map(&tm_pull);
    }
    if (threadIdx.x >> 5 == 8) {
        if (threadIdx.x == 256) {
#pragma unroll
            for (int b = 0; b < 7; b++) mbar_init(sb + kWBarOff + 8 * b, 1);
            asm volatile("fence.proxy.async.shared::cta;" ::: "memory");
        }
        __syncwarp();
        named_bar_arrive(8, 384);
        if (threadIdx.x == 256) {
            mbar_expect_tx(sb + kDwBarOff, kC * 2);
            asm volatile("cp.async.bulk.shared::cluster.global.mbarrier::complete_tx::bytes [%0], [%1], %2, [%3];"
                         ::"r"(sb + kDwOff), "l"(dw), "r"(kC * 2), "r"(sb + kDwBarOff) : "memory");
#pragma unroll
            for (int j = 0; j < 3; j++) {
                mbar_expect_tx(sb + kWBarOff + 8 * j, 2 * kWChunkBytes);
#pragma unroll
                for (int c = 2 * j; c < 2 * j + 2; c++)
                    asm volatile("cp.async.bulk.tensor.3d.shared::cluster.global.mbarrier::complete_tx::bytes [%0], [%1, {%3, %4, %5}], [%2];"
                                 ::"r"(sb + kWOff + c * kWChunkBytes), "l"(&tm_w), "r"(sb + kWBarOff + 8 * j), "r"(0), "r"(c * 64),
                                   "r"((int)rank * 3) : "memory");
                mbar_expect_tx(sb + kXBarOff + 8 * j, kXSlabBytes);
                asm volatile("cp.async.bulk.tensor.4d.shared::cluster.global.mbarrier::complete_tx::bytes [%0], [%1, {%3, %3, %4, %5}], [%2];"
                             ::"r"(sb + j * kXSlabBytes), "l"(&tm_x0), "r"(sb + kXBarOff + 8 * j), "r"(0), "r"(2 * j),
                               "r"(cluster * 8) : "memory");
            }
        }
        __syncwarp();
    }

    if (threadIdx.x < 384) {
        asm volatile("setmaxnreg.inc.sync.aligned.u32 160;");
        cluster_arrive();
        if (threadIdx.x >> 5 != 8) named_bar_sync(8, 384);
        const int wg = __shfl_sync(0xffffffffu, threadIdx.x >> 7, 0);
        const int warp = (threadIdx.x >> 5) & 3;
        const int lane = threadIdx.x & 31;
        const int mi = lane >> 3, ri = lane & 7;
        const uint32_t leader_empty = map_to_cta(sb + kEmptyOff, 0);
        uint32_t st_off = sb + kOutOff + (((mi >> 1) * 8 + ri) * 3 + wg) * 128 + (((2 * warp + (mi & 1)) ^ ((3 * ri + wg) & 7)) << 4);
        int s = 0, ob = 0;
        uint32_t ph = 0, oph = 1;
        auto release_stage = [&]() {
            if (lane == 0) mbar_arrive_cluster(leader_empty + 8 * s);
            if (++s == kStages) { s = 0; ph ^= 1; }
        };
        auto pack = [&](uint32_t (&p)[8], const float* acc) {
#pragma unroll
            for (int k = 0; k < 8; k++) p[k] = pack_bf16(acc[2 * k], acc[2 * k + 1]);
        };
        auto put = [&](const uint32_t (&p)[8], int t) {
            mbar_wait(sb + kOEmptyOff + 8 * ob, oph);
            if (threadIdx.x == 0) sts32(sb + kOSlotOff + 4 * ob, t);
#pragma unroll
            for (int q = 0; q < 2; q++)
                asm volatile("stmatrix.sync.aligned.m8n8.x4.trans.shared.b16 [%0], {%1, %2, %3, %4};"
                             ::"r"(st_off + ob * kOutBytes + q * (16 * 384)), "r"(p[4 * q]), "r"(p[4 * q + 1]),
                               "r"(p[4 * q + 2]), "r"(p[4 * q + 3]) : "memory");
            asm volatile("fence.proxy.async.shared::cta;" ::: "memory");
            __syncwarp();
            if (lane == 0) mbar_arrive(sb + kOFullOff + 8 * ob);
            if (++ob == kOutBufs) { ob = 0; oph ^= 1; }
        };
        auto my_turn = [&]() { named_bar_sync(2 + wg, 256); };
        auto pass_turn = [&]() { named_bar_arrive(wg == 2 ? 2 : 3 + wg, 256); };
        if (wg == 2) pass_turn();

        uint32_t a[24][4];
        {
            float acc0[32];
            uint32_t dws[48];
            mbar_wait(sb + kDwBarOff, 0);
#pragma unroll
            for (int k = 0; k < 48; k++) dws[k] = lds32(sb + kDwOff + k * 16 + (lane & 3) * 4);
            cluster_wait();
            if (lane < 3) mbar_arrive_cluster(leader_empty + 8 * lane);
            const uint32_t wbase = sb + kWOff + wg * 8192 + ((mi >> 1) * 8 + ri) * 128 + (((2 * warp + (mi & 1)) ^ ri) << 4);
            const uint64_t desc = make_desc(sb, 2048);
#pragma unroll
            for (int j = 0; j < 3; j++) {
                mbar_wait(sb + kWBarOff + 8 * j, 0);
#pragma unroll
                for (int k = 8 * j; k < 8 * j + 8; k++) {
                    asm volatile("ldmatrix.sync.aligned.m8n8.x4.trans.shared.b16 {%0, %1, %2, %3}, [%4];"
                                 : "=r"(a[k][0]), "=r"(a[k][1]), "=r"(a[k][2]), "=r"(a[k][3])
                                 : "r"(wbase + (k >> 2) * kWChunkBytes + (k & 3) * 2048) : "memory");
                    a[k][0] = mul_bf16x2(a[k][0], dws[2 * k]);
                    a[k][1] = mul_bf16x2(a[k][1], dws[2 * k]);
                    a[k][2] = mul_bf16x2(a[k][2], dws[2 * k + 1]);
                    a[k][3] = mul_bf16x2(a[k][3], dws[2 * k + 1]);
                }
                uint32_t dep = 0;
#pragma unroll
                for (int k = 8 * j; k < 8 * j + 8; k++) dep ^= a[k][3];
                dep &= num_tiles >> 24;
                if (j == 0 && lane >= 3 && lane < kStages) mbar_arrive_cluster(leader_empty + 8 * lane + dep);
                if (j == 2) {
                    named_bar_arrive((wg == 0 ? 6 : 5) + dep, 384);
                    named_bar_arrive(wg == 2 ? 6 : 7, 384);
                }
                mbar_wait(sb + kXBarOff + 8 * j, 0);
                my_turn();
                asm volatile("wgmma.fence.sync.aligned;" ::: "memory");
#pragma unroll
                for (int k = 0; k < 8; k++) wgmma_rs(acc0, a[8 * j + k], desc + (j * kXSlabBytes >> 4) + desc_k(k), j + k != 0);
                pass_turn();
            }
            asm volatile("wgmma.commit_group.sync.aligned;" ::: "memory");
            named_bar_sync(5 + wg, 384);
            asm volatile("wgmma.wait_group.sync.aligned 0;" ::: "memory");
            release_stage();
            release_stage();
            uint32_t p[8];
            pack(p, acc0);
            put(p, static_tile(0));
            pack(p, acc0 + 16);
            put(p, static_tile(1));
        }

        float acc[16];
        uint32_t park[kPark][8], park_last;
        int parked = 0;
        st_off += num_tiles >> 24;
        auto spill_addr = [&](int base, int shift, int zero) {
            return ((st_off + zero) >> shift) + (sb - (sb >> shift) + kSpillOff + base - (kOutOff >> shift));
        };
        asm volatile("mov.b32 %0, 0;" : "=r"(park_last));
#pragma unroll
        for (int k = 0; k < kPark * 8; k++) asm volatile("mov.b32 %0, 0;" : "=r"(park[k / 8][k % 8]));
#pragma unroll 1
        while (true) {
            mbar_wait(sb + kFullOff + 8 * s, ph);
            const int t = lds32(sb + kSlotOff + 4 * s);
            if (t >= num_tiles) break;
            const uint64_t desc = make_desc(sb + s * kStageBytes, 6144);
            my_turn();
            asm volatile("wgmma.fence.sync.aligned;" ::: "memory");
#pragma unroll
            for (int k = 0; k < 24; k++) {
                if (k == 19) pass_turn();
                wgmma_rs(acc, a[k], desc + desc_k(k), k != 0);
            }
            asm volatile("wgmma.commit_group.sync.aligned;" ::: "memory");
            asm volatile("wgmma.wait_group.sync.aligned 0;" ::: "memory");
            release_stage();
            const int keep = t >= park_from ? kPark + 1 : t >= mid_from && t < mid_to ? mid_n : 0;
            if (parked < keep) {
#pragma unroll
                for (int k = 0; k < kPark; k++)
                    if (parked == k) pack(park[k], acc);
                if (parked == kPark) {
                    uint32_t p[8];
                    pack(p, acc);
                    mbar_wait(sb + kPullBarOff, 0);
                    asm volatile("st.shared.v4.b32 [%0], {%1, %2, %3, %4};"
                                 ::"r"(spill_addr(0, 0, 0)), "r"(p[0]), "r"(p[1]), "r"(p[2]), "r"(p[3]) : "memory");
                    asm volatile("st.shared.v2.b32 [%0], {%1, %2};" ::"r"(spill_addr(6144, 1, t >> 24)), "r"(p[4]), "r"(p[5]) : "memory");
                    sts32(spill_addr(9216, 2, t >> 24), p[6]);
                    asm volatile("xor.b32 %0, %1, %2;" : "=r"(park_last) : "r"(p[7]), "r"(st_off));
                }
                if (threadIdx.x == 0) sts32(sb + kPSlotOff + 4 * parked, t);
                parked++;
            } else {
                uint32_t p[8];
                pack(p, acc);
                put(p, t);
                if (parked > keep) {
#pragma unroll
                    for (int k = 2; k >= 0; k--)
                        if (k < parked) put(park[k], threadIdx.x == 0 ? lds32(sb + kPSlotOff + 4 * k) : 0);
                    parked = 0;
                }
            }
        }
#pragma unroll
        for (int k = 0; k < kPark; k++)
            if (k < parked) put(park[k], threadIdx.x == 0 ? lds32(sb + kPSlotOff + 4 * k) : 0);
        if (parked > kPark) {
            uint32_t p[8];
            asm volatile("ld.shared.v4.b32 {%0, %1, %2, %3}, [%4];"
                         : "=r"(p[0]), "=r"(p[1]), "=r"(p[2]), "=r"(p[3]) : "r"(spill_addr(0, 0, 0)) : "memory");
            asm volatile("ld.shared.v2.b32 {%0, %1}, [%2];" : "=r"(p[4]), "=r"(p[5]) : "r"(spill_addr(6144, 1, parked >> 24)) : "memory");
            p[6] = lds32(spill_addr(9216, 2, parked >> 24));
            asm volatile("xor.b32 %0, %1, %2;" : "=r"(p[7]) : "r"(park_last), "r"(st_off));
            put(p, threadIdx.x == 0 ? lds32(sb + kPSlotOff + 4 * kPark) : 0);
        }
        mbar_wait(sb + kPullBarOff, 0);
        mbar_wait(sb + kOEmptyOff + 8 * ob, oph);
        if (threadIdx.x == 0) sts32(sb + kOSlotOff + 4 * ob, num_tiles);
        __syncwarp();
        if (lane == 0) mbar_arrive(sb + kOFullOff + 8 * ob);
    } else {
        asm volatile("setmaxnreg.dec.sync.aligned.u32 32;");
        const int role = __shfl_sync(0xffffffffu, (threadIdx.x >> 5) & 3, 0);
        const bool lead = (threadIdx.x & 31) == 0;
        if (role >= 2) {
            if (lead) {
                if (role == 2) {
#pragma unroll
                    for (int b = 0; b < kOutBufs; b++) {
                        mbar_init(sb + kOFullOff + 8 * b, 12);
                        mbar_init(sb + kOEmptyOff + 8 * b, 1);
                    }
                } else {
#pragma unroll
                    for (int s = 0; s < kStages; s++) {
                        mbar_init(sb + kFullOff + 8 * s, 1);
                        mbar_init(sb + kEmptyOff + 8 * s, 24);
                        if (s < 2) mbar_arrive(sb + kFullOff + 8 * s);
                    }
                    prefetch_map(&tm_x);
                    prefetch_map(&tm_o);
                }
                asm volatile("fence.mbarrier_init.release.cluster;" ::: "memory");
            }
            cluster_arrive();
            cluster_wait();
            if (role == 2) {
                uint64_t normal, streaming;
                asm volatile("createpolicy.fractional.L2::evict_normal.b64 %0, 1.0;" : "=l"(normal));
                asm volatile("createpolicy.fractional.L2::evict_first.b64 %0, 1.0;" : "=l"(streaming));
                int head = 0, tail = 0, freed = 0, n = 0, held = 0, pos = 0, k = 0, hold = 0, next = 0;
                uint32_t ph = 0;
                auto issue = [&](int u) {
                    if (lead) {
                        asm volatile("cp.async.bulk.tensor.3d.global.shared::cta.bulk_group.L2::cache_hint [%0, {%2, %3, %4}], [%1], %5;"
                                     ::"l"(&tm_o), "r"(sb + kOutOff + tail * kOutBytes), "r"(0), "r"((int)rank * 3),
                                       "r"(u * kTilePx), "l"(pos >= stream_from ? streaming : normal) : "memory");
                        asm volatile("cp.async.bulk.commit_group;" ::: "memory");
                    }
                    tail = (tail + 1) & (kOutBufs - 1);
                    held--;
                    n++;
                };
#pragma unroll 1
                while (true) {
                    const bool push = held > 0 && held >= hold;
                    const int oldest = __shfl_sync(0xffffffffu, lds32(sb + kOSlotOff + 4 * tail), 0);
                    mbar_wait(sb + kOFullOff + 8 * head, ph);
                    if (push) issue(oldest);
                    const int t = __shfl_sync(0xffffffffu, lds32(sb + kOSlotOff + 4 * head), 0);
                    int lag = 0;
                    if (t < num_tiles) {
                        held++;
                        pos = max(pos, t);
                        if (++head == kOutBufs) { head = 0; ph ^= 1; }
#pragma unroll 1
                        while (pos >= next) {
                            hold = kn.hold[k++];
                            next = k < kHoldPts ? kn.hold_pos[k] : 0x7fffffff;
                        }
                        lag = hold < 6 ? kn.lag : 0;
                    } else {
                        hold = 0;
                    }
#pragma unroll 1
                    while (held > hold) issue(lds32(sb + kOSlotOff + 4 * tail));
#pragma unroll 1
                    for (; n > lag; n--) {
                        if (lead) {
                            if (n == 1) asm volatile("cp.async.bulk.wait_group.read 0;" ::: "memory");
                            else if (n == 2) asm volatile("cp.async.bulk.wait_group.read 1;" ::: "memory");
                            else if (n <= 4) asm volatile("cp.async.bulk.wait_group.read 2;" ::: "memory");
                            else asm volatile("cp.async.bulk.wait_group.read 4;" ::: "memory");
                            mbar_arrive(sb + kOEmptyOff + 8 * freed);
                        }
                        freed = (freed + 1) & (kOutBufs - 1);
                    }
                    if (t >= num_tiles) break;
                }
            }
        } else if (role == 1) {
            const uint32_t t_start = __shfl_sync(0xffffffffu, globaltimer(), 0);
            const uint32_t my_slot = sb + kSlotOff + 4 * min(threadIdx.x & 31, kStages - 1);
            sts32(my_slot, 0);
            __threadfence_block();
            cluster_arrive();
            int k = 0;
#pragma unroll 1
            for (int t = blockIdx.x + gridDim.x; t < num_tiles; t += gridDim.x) {
                if (t < kn.pf_from) continue;
                const uint32_t due = kn.pf_t0 + (t - gridDim.x) * kn.pf_dt / gridDim.x;
                for (int n = 0; globaltimer() - t_start < due && n < 4096; n++) __nanosleep(50);
#pragma unroll 1
                while (k + 1 < kLeadPts && t >= kn.lead_pos[k + 1]) k++;
                const int max_lead = kn.lead[k] + ((t - kn.lead_pos[k]) * kn.lead_slope[k] >> 16);
                for (int n = 0; t > max_lead && n < 4096; n++) {
                    const int front = __reduce_max_sync(0xffffffffu, lds32_volatile(my_slot));
                    if (t - max_lead <= front || front >= num_tiles) break;
                    __nanosleep(50);
                }
                if (lead)
                    asm volatile("cp.async.bulk.prefetch.L2.global [%0], %1;"
                                 ::"l"((const char*)x + (size_t)t * kStageBytes), "r"(kStageBytes) : "memory");
            }
            cluster_wait();
        } else {
            const uint32_t t_start = __shfl_sync(0xffffffffu, globaltimer(), 0);
            if (lead) {
                mbar_init(sb + kPullBarOff, 1);
                asm volatile("fence.proxy.async.shared::cta;" ::: "memory");
                mbar_expect_tx(sb + kPullBarOff, rank * 3072 * kn.pull_n);
            }
            __threadfence_block();
            cluster_arrive();
            if (__shfl_sync(0xffffffffu, rank, 0) == 1) {
#pragma unroll 1
                for (int i = 0; i < kn.pull_n; i++) {
                    const uint32_t due = kn.pull_t0 + (i * gridDim.x + blockIdx.x) * kn.pull_dt / gridDim.x;
                    for (int n = 0; globaltimer() - t_start < due && n < 4096; n++) {}
                    if (lead)
                        asm volatile("cp.async.bulk.tensor.2d.shared::cluster.global.mbarrier::complete_tx::bytes [%0], [%1, {%3, %4}], [%2];"
                                     ::"r"(sb + kScratchOff), "l"(&tm_pull), "r"(sb + kPullBarOff), "r"(0),
                                       "r"(static_tile(i + 2) * 192) : "memory");
                }
            }
            cluster_wait();
            if (__shfl_sync(0xffffffffu, rank, 0) == 0) {
                const uint32_t peer = map_to_cta(sb, 1);
                const int nstatic = static_tiles * (gridDim.x >> 1);
                const unsigned last_fetch = num_tiles - nstatic + gridDim.x - 1;
                mbar_wait(sb + kEmptyOff, 0);
                mbar_wait(sb + kEmptyOff + 8, 0);
                int s = 2, g = 0, gap = 0, gap_next = 0;
                uint32_t earliest = 0;
                uint32_t ph = 0;
                auto fetch = [&](unsigned& raw) {
                    if (lead) asm volatile("atom.global.inc.u32 %0, [%1], %2;" : "=r"(raw) : "l"(&g_tile_counter), "r"(last_fetch) : "memory");
                };
                auto load = [&](int t, bool valid) {
                    mbar_wait(sb + kEmptyOff + 8 * s, ph);
                    __syncwarp();
                    if (gap) {
                        uint32_t now = globaltimer() - t_start;
                        for (int n = 0; now < earliest && n < 4096; n++) now = globaltimer() - t_start;
                        earliest = max(earliest, now - kn.slack) + gap;
                    }
                    const uint32_t full = kFullOff + 8 * s, slot = kSlotOff + 4 * s;
                    const uint32_t bytes = valid ? kStageBytes : 0;
                    if (lead && valid)
                        asm volatile(
                            "cp.async.bulk.tensor.4d.shared::cluster.global.mbarrier::complete_tx::bytes.multicast::cluster "
                            "[%0], [%1, {%3, %3, %3, %4}], [%2], %5;"
                            ::"r"(sb + s * kStageBytes), "l"(&tm_x), "r"(sb + full), "r"(0), "r"(t * (kTilePx / 8)),
                              "h"((uint16_t)3) : "memory");
                    if (lead) {
                        sts32(sb + slot, t);
                        mbar_expect_tx(sb + full, bytes);
                        asm volatile("mbarrier.arrive.expect_tx.shared::cluster.b64 _, [%0], %1;" ::"r"(peer + full), "r"(bytes + 4) : "memory");
                        asm volatile("st.async.weak.shared::cluster.mbarrier::complete_tx::bytes.b32 [%0], %1, [%2];"
                                     ::"r"(peer + slot), "r"(t), "r"(peer + full) : "memory");
                    }
                    if (++s == kStages) { s = 0; ph ^= 1; }
#pragma unroll 1
                    while (t >= gap_next) {
                        gap = kn.gap[g++];
                        gap_next = g < kGapPts ? kn.gap_pos[g] : 0x7fffffff;
                    }
                };
                unsigned raw0 = 0, raw1 = 0;
#pragma unroll 1
                for (int i = 2; i < static_tiles; i++) {
                    if (i == static_tiles - 2) fetch(raw0);
                    if (i == static_tiles - 1) fetch(raw1);
                    load(static_tile(i), true);
                }
                auto step = [&](unsigned& raw) -> bool {
                    const int t = nstatic + __shfl_sync(0xffffffffu, raw, 0);
                    const bool valid = t < num_tiles;
                    if (valid) fetch(raw);
                    load(t, valid);
                    return valid;
                };
#pragma unroll 1
                while (step(raw0) && step(raw1)) {}
#pragma unroll 1
                for (int k = 1; k < kStages; k++) {
                    mbar_wait(sb + kEmptyOff + 8 * s, ph);
                    if (++s == kStages) { s = 0; ph ^= 1; }
                }
            }
        }
    }
}

typedef CUresult (*EncodeTiledFn)(CUtensorMap*, CUtensorMapDataType, cuuint32_t, void*, const cuuint64_t*,
                                  const cuuint64_t*, const cuuint32_t*, const cuuint32_t*, CUtensorMapInterleave,
                                  CUtensorMapSwizzle, CUtensorMapL2promotion, CUtensorMapFloatOOBfill);

}

extern "C" void kernel_launch(void* const* d_in, const int* in_sizes, int n_in, void* d_out, int out_size) {
    (void)n_in; (void)out_size;
    const __nv_bfloat16* x = (const __nv_bfloat16*)d_in[0];
    const __nv_bfloat16* dw = (const __nv_bfloat16*)d_in[1];
    const __nv_bfloat16* pw = (const __nv_bfloat16*)d_in[2];
    const int pixels = in_sizes[0] / kC;

    static EncodeTiledFn encode = nullptr;
    static int grid = 0;
    if (!encode) {
        void* fn = nullptr;
        cudaDriverEntryPointQueryResult qr;
        cudaGetDriverEntryPoint("cuTensorMapEncodeTiled", &fn, cudaEnableDefault, &qr);
        encode = (EncodeTiledFn)fn;
        cudaFuncSetAttribute(dwsep_kernel, cudaFuncAttributeMaxDynamicSharedMemorySize, kSmemBytes);
        int sms = 0, clusters = 0;
        cudaDeviceGetAttribute(&sms, cudaDevAttrMultiProcessorCount, 0);
        cudaLaunchConfig_t cfg = {};
        cudaLaunchAttribute attr = {};
        attr.id = cudaLaunchAttributeClusterDimension;
        attr.val.clusterDim.x = 2;
        attr.val.clusterDim.y = attr.val.clusterDim.z = 1;
        cfg.gridDim = dim3(sms & ~1);
        cfg.blockDim = dim3(kThreads);
        cfg.dynamicSmemBytes = kSmemBytes;
        cfg.attrs = &attr;
        cfg.numAttrs = 1;
        if (cudaOccupancyMaxActiveClusters(&clusters, dwsep_kernel, &cfg) != cudaSuccess || clusters < 1) {
            (void)cudaGetLastError();
            clusters = sms / 2;
        }
        grid = 2 * (clusters < sms / 2 ? clusters : sms / 2);
    }

    CUtensorMap tm_w, tm_x0, tm_x, tm_o, tm_pull;
    auto make_map = [&](CUtensorMap* m, const void* base, int rank, const cuuint64_t* dims, const cuuint64_t* strides,
                        const cuuint32_t* box, CUtensorMapL2promotion promo) {
        const cuuint32_t ones[4] = {1, 1, 1, 1};
        encode(m, CU_TENSOR_MAP_DATA_TYPE_BFLOAT16, rank, (void*)base, dims, strides, box, ones,
               CU_TENSOR_MAP_INTERLEAVE_NONE, CU_TENSOR_MAP_SWIZZLE_128B, promo, CU_TENSOR_MAP_FLOAT_OOB_FILL_NONE);
    };
    {
        const cuuint64_t dims[3] = {64, kC, 6}, strides[2] = {kC * 2, 128};
        const cuuint32_t box[3] = {64, 64, 3};
        make_map(&tm_w, pw, 3, dims, strides, box, CU_TENSOR_MAP_L2_PROMOTION_L2_128B);
    }
    {
        const cuuint64_t dims[4] = {64, 8, 6, (cuuint64_t)pixels / 8}, strides[3] = {kC * 2, 128, kC * 2 * 8};
        const cuuint32_t box0[4] = {64, 8, 2, 8}, box[4] = {64, 8, 6, kTilePx / 8};
        make_map(&tm_x0, x, 4, dims, strides, box0, CU_TENSOR_MAP_L2_PROMOTION_L2_128B);
        make_map(&tm_x, x, 4, dims, strides, box, CU_TENSOR_MAP_L2_PROMOTION_L2_128B);
    }
    {
        const cuuint64_t dims[3] = {64, 6, (cuuint64_t)pixels}, strides[2] = {128, kC * 2};
        const cuuint32_t box[3] = {64, 3, kTilePx};
        make_map(&tm_o, d_out, 3, dims, strides, box, CU_TENSOR_MAP_L2_PROMOTION_NONE);
    }
    {
        const cuuint64_t dims[2] = {64, (cuuint64_t)pixels * 6}, strides[1] = {128};
        const cuuint32_t box[2] = {8, 192}, ones[2] = {1, 1};
        encode(&tm_pull, CU_TENSOR_MAP_DATA_TYPE_BFLOAT16, 2, (void*)x, dims, strides, box, ones, CU_TENSOR_MAP_INTERLEAVE_NONE,
               CU_TENSOR_MAP_SWIZZLE_NONE, CU_TENSOR_MAP_L2_PROMOTION_L2_128B, CU_TENSOR_MAP_FLOAT_OOB_FILL_NONE);
    }
    Knobs kn = g_knobs;
    for (int k = 0; k < kLeadPts; k++)
        kn.lead_slope[k] = k < kLeadPts - 1 ? (kn.lead[k + 1] - kn.lead[k]) * 65536 / (kn.lead_pos[k + 1] - kn.lead_pos[k]) : 0;
    dwsep_kernel<<<grid, kThreads, kSmemBytes, cudaStreamPerThread>>>(tm_w, tm_x0, tm_x, tm_o, tm_pull, x, dw, pw,
                                                                      pixels / kTilePx, kn.mid_from, kn.mid_to, kn.mid_n,
                                                                      kn.park_from, kn.static_tiles, kn.stream_from, kn);
}
```

```cpp
#include <cuda_runtime.h>
#include <cuda_bf16.h>
#include <cuda.h>
#include <stdint.h>

namespace {

constexpr int kC = 384;
constexpr int kTilePx = 32;
constexpr int kStages = 5;
constexpr int kOutBufs = 8;
constexpr int kPark = 5;
constexpr int kThreads = 512;
constexpr int kStageBytes = kTilePx * kC * 2;
constexpr int kOutBytes = kTilePx * 192 * 2;
constexpr int kWChunkBytes = 64 * 192 * 2;
constexpr int kXSlabBytes = 64 * 128 * 2;
constexpr int kWOff = 3 * kStageBytes;
constexpr int kOutOff = kStages * kStageBytes;
constexpr int kSpillOff = kOutOff + kOutBufs * kOutBytes;
constexpr int kDwOff = kSpillOff;
constexpr int kScratchOff = kSpillOff + 1024;
constexpr int kFullOff = kSpillOff + 384 * 28;
constexpr int kEmptyOff = kFullOff + 8 * kStages;
constexpr int kOFullOff = kEmptyOff + 8 * kStages;
constexpr int kOEmptyOff = kOFullOff + 8 * kOutBufs;
constexpr int kWBarOff = kOEmptyOff + 8 * kOutBufs;
constexpr int kXBarOff = kWBarOff + 8 * 3;
constexpr int kDwBarOff = kXBarOff + 8 * 3;
constexpr int kPullBarOff = kDwBarOff + 8;
constexpr int kSlotOff = kPullBarOff + 8;
constexpr int kOSlotOff = kSlotOff + 4 * kStages;
constexpr int kPSlotOff = kOSlotOff + 4 * kOutBufs;
constexpr int kSmemBytes = kPSlotOff + 4 * (kPark + 1);
static_assert(kWChunkBytes == kStageBytes && kWOff + 6 * kWChunkBytes <= kDwOff, "weight staging");
static_assert(kSmemBytes <= 232448, "shared memory");

constexpr int kGapPts = 6, kHoldPts = 12, kLeadPts = 10;
struct Knobs {
    int first_gap;
    int pull_n, pull_t0, pull_dt;
    int pf_from, pf_t0, pf_dt;
    int static_tiles;
    int mid_from, mid_to, mid_n;
    int park_from;
    int stream_from;
    int lag;
    int slack;
    int gap_pos[kGapPts], gap[kGapPts];
    int hold_pos[kHoldPts], hold[kHoldPts];
    int lead_pos[kLeadPts], lead[kLeadPts];
    int lead_slope[kLeadPts];
};
#define DEFAULT_KNOBS {518, 5, 67, 398, 594, 239, 654, 20, 1590, 3275, 2, 3414, 4264, 2, 241, \
    {0, 300, 1894, 2523, 3277, 3954}, {0, 0, 858, 974, 811, 0}, \
    {0, 378, 456, 594, 599, 956, 968, 1903, 3000, 4245, 4382, 4608}, {0, 1, 2, 3, 4, 5, 6, 7, 7, 4, 2, 2}, \
    {0, 847, 1450, 1994, 2090, 2316, 3660, 3809, 3904, 4471}, {243, 373, 539, 337, 389, 328, 134, 201, 243, 154}}
constexpr Knobs g_knobs = DEFAULT_KNOBS;

__device__ unsigned int g_tile_counter;

__device__ __forceinline__ uint32_t smem_u32(const void* p) { return (uint32_t)__cvta_generic_to_shared(p); }

__device__ __forceinline__ void mbar_init(uint32_t bar, uint32_t cnt) {
    asm volatile("mbarrier.init.shared::cta.b64 [%0], %1;" ::"r"(bar), "r"(cnt) : "memory");
}
__device__ __forceinline__ void mbar_expect_tx(uint32_t bar, uint32_t bytes) {
    asm volatile("mbarrier.arrive.expect_tx.shared::cta.b64 _, [%0], %1;" ::"r"(bar), "r"(bytes) : "memory");
}
__device__ __forceinline__ void mbar_arrive(uint32_t bar) {
    asm volatile("mbarrier.arrive.shared::cta.b64 _, [%0];" ::"r"(bar) : "memory");
}
__device__ __forceinline__ void mbar_arrive_cluster(uint32_t bar) {
    asm volatile("mbarrier.arrive.shared::cluster.b64 _, [%0];" ::"r"(bar) : "memory");
}
__device__ __forceinline__ void mbar_wait(uint32_t bar, uint32_t parity) {
    asm volatile(
        "{\n.reg .pred p;\n.reg .u32 n;\n"
        "mbarrier.try_wait.parity.shared::cta.b64 p, [%0], %1;\n"
        "@p bra DONE;\n"
        "mov.u32 n, 0;\n"
        "LOOP:\n"
        "mbarrier.try_wait.parity.shared::cta.b64 p, [%0], %1;\n"
        "@p bra DONE;\n"
        "add.u32 n, n, 1;\n"
        "setp.lt.u32 p, n, 4194304;\n"
        "@p bra LOOP;\n"
        "trap;\n"
        "DONE:\n}" ::"r"(bar), "r"(parity) : "memory");
}
__device__ __forceinline__ uint32_t map_to_cta(uint32_t addr, uint32_t cta) {
    uint32_t r;
    asm("mapa.shared::cluster.u32 %0, %1, %2;" : "=r"(r) : "r"(addr), "r"(cta));
    return r;
}
__device__ __forceinline__ void named_bar_sync(int id, int n) { asm volatile("bar.sync %0, %1;" ::"r"(id), "r"(n) : "memory"); }
__device__ __forceinline__ void named_bar_arrive(int id, int n) { asm volatile("bar.arrive %0, %1;" ::"r"(id), "r"(n) : "memory"); }
__device__ __forceinline__ void cluster_arrive() {
    __syncwarp();
    asm volatile("barrier.cluster.arrive.relaxed.aligned;" ::: "memory");
}
__device__ __forceinline__ void cluster_wait() {
    __syncwarp();
    asm volatile("barrier.cluster.wait.acquire.aligned;" ::: "memory");
}
__device__ __forceinline__ void prefetch_line(const void* p) { asm volatile("prefetch.global.L2 [%0];" ::"l"(p) : "memory"); }
__device__ __forceinline__ void prefetch_map(const CUtensorMap* m) { asm volatile("prefetch.tensormap [%0];" ::"l"(m) : "memory"); }
__device__ __forceinline__ uint32_t globaltimer() {
    uint32_t t;
    asm volatile("mov.u32 %0, %%globaltimer_lo;" : "=r"(t));
    return t;
}
__device__ __forceinline__ uint32_t clock32() {
    uint32_t t;
    asm volatile("mov.u32 %0, %%clock;" : "=r"(t));
    return t;
}
__device__ __forceinline__ int lds32(uint32_t addr) {
    int v;
    asm volatile("ld.shared.b32 %0, [%1];" : "=r"(v) : "r"(addr) : "memory");
    return v;
}
__device__ __forceinline__ int lds32_volatile(uint32_t addr) {
    int v;
    asm volatile("ld.volatile.shared.b32 %0, [%1];" : "=r"(v) : "r"(addr) : "memory");
    return v;
}
__device__ __forceinline__ void sts32(uint32_t addr, int v) { asm volatile("st.shared.b32 [%0], %1;" ::"r"(addr), "r"(v) : "memory"); }

#define ACC4(o) "+f"(d[o]), "+f"(d[o + 1]), "+f"(d[o + 2]), "+f"(d[o + 3])
#define ACC16(o) ACC4(o), ACC4(o + 4), ACC4(o + 8), ACC4(o + 12)
__device__ __forceinline__ void wgmma_rs(float (&d)[32], const uint32_t (&a)[4], uint64_t desc_b, int scale_d) {
    asm volatile(
        "{\n.reg .pred p;\nsetp.ne.b32 p, %37, 0;\n"
        "wgmma.mma_async.sync.aligned.m64n64k16.f32.bf16.bf16 "
        "{%0, %1, %2, %3, %4, %5, %6, %7, %8, %9, %10, %11, %12, %13, %14, %15, "
        "%16, %17, %18, %19, %20, %21, %22, %23, %24, %25, %26, %27, %28, %29, %30, %31}, "
        "{%32, %33, %34, %35}, %36, p, 1, 1, 0;\n}"
        : ACC16(0), ACC16(16)
        : "r"(a[0]), "r"(a[1]), "r"(a[2]), "r"(a[3]), "l"(desc_b), "r"(scale_d));
}
__device__ __forceinline__ void wgmma_rs(float (&d)[16], const uint32_t (&a)[4], uint64_t desc_b, int scale_d) {
    asm volatile(
        "{\n.reg .pred p;\nsetp.ne.b32 p, %21, 0;\n"
        "wgmma.mma_async.sync.aligned.m64n32k16.f32.bf16.bf16 "
        "{%0, %1, %2, %3, %4, %5, %6, %7, %8, %9, %10, %11, %12, %13, %14, %15}, "
        "{%16, %17, %18, %19}, %20, p, 1, 1, 0;\n}"
        : ACC16(0)
        : "r"(a[0]), "r"(a[1]), "r"(a[2]), "r"(a[3]), "l"(desc_b), "r"(scale_d));
}
__device__ __forceinline__ uint64_t make_desc(uint32_t addr, uint32_t group_stride) {
    return (uint64_t(1) << 62) | (uint64_t(group_stride >> 4) << 32) | (uint64_t(1) << 16) | (uint64_t)((addr & 0x3FFFF) >> 4);
}
__device__ __forceinline__ constexpr uint64_t desc_k(int k) { return (uint64_t)(((k >> 2) * 1024 + (k & 3) * 32) >> 4); }

__device__ __forceinline__ uint32_t pack_bf16(float lo, float hi) {
    uint32_t r;
    asm("cvt.rn.bf16x2.f32 %0, %1, %2;" : "=r"(r) : "f"(hi), "f"(lo));
    return r;
}
__device__ __forceinline__ uint32_t mul_bf16x2(uint32_t a, uint32_t b) {
    uint32_t r;
    asm("mul.rn.bf16x2 %0, %1, %2;" : "=r"(r) : "r"(a), "r"(b));
    return r;
}

__global__ void __cluster_dims__(2, 1, 1) __launch_bounds__(kThreads, 1)
dwsep_kernel(const __grid_constant__ CUtensorMap tm_w, const __grid_constant__ CUtensorMap tm_x0,
             const __grid_constant__ CUtensorMap tm_x, const __grid_constant__ CUtensorMap tm_o,
             const __grid_constant__ CUtensorMap tm_pull,
             const __nv_bfloat16* __restrict__ x, const __nv_bfloat16* __restrict__ dw,
             const __nv_bfloat16* __restrict__ pw, int num_tiles,
             int mid_from, int mid_to, int mid_n, int park_from, int static_tiles, int stream_from,
             const __grid_constant__ Knobs kn) {
    extern __shared__ __align__(1024) uint8_t smem_raw[];
    const uint32_t sb = smem_u32(smem_raw);

    uint32_t rank;
    asm("mov.u32 %0, %%cluster_ctarank;" : "=r"(rank));
    const int cluster = blockIdx.x >> 1;
    auto static_tile = [&](int i) { return (i >> 1) * gridDim.x + cluster * 2 + (i & 1); };

    if (threadIdx.x < 32) {
        prefetch_line(threadIdx.x < 18 ? (const char*)pw + (blockIdx.x & 127) * 2304 + threadIdx.x * 128
                                       : (const char*)dw + min(threadIdx.x - 18, 5) * 128);
    } else if (threadIdx.x < 224) {
        const uint32_t c0 = __shfl_sync(0xffffffffu, clock32(), 0), chunk = (threadIdx.x >> 5) - 1;
        const uint32_t delay = ((chunk >> 1) * gridDim.x + blockIdx.x) * kn.first_gap >> 7;
        for (int n = 0; clock32() - c0 < delay && n < 1024; n++) {}
        prefetch_line((const char*)x + (size_t)blockIdx.x * kStageBytes + (threadIdx.x & 31) * 768 + chunk * 128);
    } else if (threadIdx.x == 288) {
        prefetch_map(&tm_w);
        prefetch_map(&tm_x0);
        if (rank == 1) prefetch_map(&tm_pull);
    }
    if (threadIdx.x >> 5 == 8) {
        if (threadIdx.x == 256) {
#pragma unroll
            for (int b = 0; b < 7; b++) mbar_init(sb + kWBarOff + 8 * b, 1);
            asm volatile("fence.proxy.async.shared::cta;" ::: "memory");
        }
        __syncwarp();
        named_bar_arrive(8, 384);
        if (threadIdx.x == 256) {
            mbar_expect_tx(sb + kDwBarOff, kC * 2);
            asm volatile("cp.async.bulk.shared::cluster.global.mbarrier::complete_tx::bytes [%0], [%1], %2, [%3];"
                         ::"r"(sb + kDwOff), "l"(dw), "r"(kC * 2), "r"(sb + kDwBarOff) : "memory");
#pragma unroll
            for (int j = 0; j < 3; j++) {
                mbar_expect_tx(sb + kWBarOff + 8 * j, 2 * kWChunkBytes);
#pragma unroll
                for (int c = 2 * j; c < 2 * j + 2; c++)
                    asm volatile("cp.async.bulk.tensor.3d.shared::cluster.global.mbarrier::complete_tx::bytes [%0], [%1, {%3, %4, %5}], [%2];"
                                 ::"r"(sb + kWOff + c * kWChunkBytes), "l"(&tm_w), "r"(sb + kWBarOff + 8 * j), "r"(0), "r"(c * 64),
                                   "r"((int)rank * 3) : "memory");
                mbar_expect_tx(sb + kXBarOff + 8 * j, kXSlabBytes);
                asm volatile("cp.async.bulk.tensor.4d.shared::cluster.global.mbarrier::complete_tx::bytes [%0], [%1, {%3, %3, %4, %5}], [%2];"
                             ::"r"(sb + j * kXSlabBytes), "l"(&tm_x0), "r"(sb + kXBarOff + 8 * j), "r"(0), "r"(2 * j),
                               "r"(cluster * 8) : "memory");
            }
        }
        __syncwarp();
    }

    if (threadIdx.x < 384) {
        asm volatile("setmaxnreg.inc.sync.aligned.u32 160;");
        cluster_arrive();
        if (threadIdx.x >> 5 != 8) named_bar_sync(8, 384);
        const int wg = __shfl_sync(0xffffffffu, threadIdx.x >> 7, 0);
        const int warp = (threadIdx.x >> 5) & 3;
        const int lane = threadIdx.x & 31;
        const int mi = lane >> 3, ri = lane & 7;
        const uint32_t leader_empty = map_to_cta(sb + kEmptyOff, 0);
        uint32_t st_off = sb + kOutOff + (((mi >> 1) * 8 + ri) * 3 + wg) * 128 + (((2 * warp + (mi & 1)) ^ ((3 * ri + wg) & 7)) << 4);
        int s = 0, ob = 0;
        uint32_t ph = 0, oph = 1;
        auto release_stage = [&]() {
            if (lane == 0) mbar_arrive_cluster(leader_empty + 8 * s);
            if (++s == kStages) { s = 0; ph ^= 1; }
        };
        auto pack = [&](uint32_t (&p)[8], const float* acc) {
#pragma unroll
            for (int k = 0; k < 8; k++) p[k] = pack_bf16(acc[2 * k], acc[2 * k + 1]);
        };
        auto put = [&](const uint32_t (&p)[8], int t) {
            mbar_wait(sb + kOEmptyOff + 8 * ob, oph);
            if (threadIdx.x == 0) sts32(sb + kOSlotOff + 4 * ob, t);
#pragma unroll
            for (int q = 0; q < 2; q++)
                asm volatile("stmatrix.sync.aligned.m8n8.x4.trans.shared.b16 [%0], {%1, %2, %3, %4};"
                             ::"r"(st_off + ob * kOutBytes + q * (16 * 384)), "r"(p[4 * q]), "r"(p[4 * q + 1]),
                               "r"(p[4 * q + 2]), "r"(p[4 * q + 3]) : "memory");
            asm volatile("fence.proxy.async.shared::cta;" ::: "memory");
            __syncwarp();
            if (lane == 0) mbar_arrive(sb + kOFullOff + 8 * ob);
            if (++ob == kOutBufs) { ob = 0; oph ^= 1; }
        };
        auto my_turn = [&]() { named_bar_sync(2 + wg, 256); };
        auto pass_turn = [&]() { named_bar_arrive(wg == 2 ? 2 : 3 + wg, 256); };
        if (wg == 2) pass_turn();

        uint32_t a[24][4];
        {
            float acc0[32];
            uint32_t dws[48];
            mbar_wait(sb + kDwBarOff, 0);
#pragma unroll
            for (int k = 0; k < 48; k++) dws[k] = lds32(sb + kDwOff + k * 16 + (lane & 3) * 4);
            cluster_wait();
            if (lane < 3) mbar_arrive_cluster(leader_empty + 8 * lane);
            const uint32_t wbase = sb + kWOff + wg * 8192 + ((mi >> 1) * 8 + ri) * 128 + (((2 * warp + (mi & 1)) ^ ri) << 4);
            const uint64_t desc = make_desc(sb, 2048);
#pragma unroll
            for (int j = 0; j < 3; j++) {
                mbar_wait(sb + kWBarOff + 8 * j, 0);
#pragma unroll
                for (int k = 8 * j; k < 8 * j + 8; k++) {
                    asm volatile("ldmatrix.sync.aligned.m8n8.x4.trans.shared.b16 {%0, %1, %2, %3}, [%4];"
                                 : "=r"(a[k][0]), "=r"(a[k][1]), "=r"(a[k][2]), "=r"(a[k][3])
                                 : "r"(wbase + (k >> 2) * kWChunkBytes + (k & 3) * 2048) : "memory");
                    a[k][0] = mul_bf16x2(a[k][0], dws[2 * k]);
                    a[k][1] = mul_bf16x2(a[k][1], dws[2 * k]);
                    a[k][2] = mul_bf16x2(a[k][2], dws[2 * k + 1]);
                    a[k][3] = mul_bf16x2(a[k][3], dws[2 * k + 1]);
                }
                uint32_t dep = 0;
#pragma unroll
                for (int k = 8 * j; k < 8 * j + 8; k++) dep ^= a[k][3];
                dep &= num_tiles >> 24;
                if (j == 0 && lane >= 3 && lane < kStages) mbar_arrive_cluster(leader_empty + 8 * lane + dep);
                if (j == 2) {
                    named_bar_arrive((wg == 0 ? 6 : 5) + dep, 384);
                    named_bar_arrive(wg == 2 ? 6 : 7, 384);
                }
                mbar_wait(sb + kXBarOff + 8 * j, 0);
                my_turn();
                asm volatile("wgmma.fence.sync.aligned;" ::: "memory");
#pragma unroll
                for (int k = 0; k < 8; k++) wgmma_rs(acc0, a[8 * j + k], desc + (j * kXSlabBytes >> 4) + desc_k(k), j + k != 0);
                pass_turn();
            }
            asm volatile("wgmma.commit_group.sync.aligned;" ::: "memory");
            named_bar_sync(5 + wg, 384);
            asm volatile("wgmma.wait_group.sync.aligned 0;" ::: "memory");
            release_stage();
            release_stage();
            uint32_t p[8];
            pack(p, acc0);
            put(p, static_tile(0));
            pack(p, acc0 + 16);
            put(p, static_tile(1));
        }

        float acc[16];
        uint32_t park[kPark][8], park_last;
        int parked = 0;
        st_off += num_tiles >> 24;
        auto spill_addr = [&](int base, int shift, int zero) {
            return ((st_off + zero) >> shift) + (sb - (sb >> shift) + kSpillOff + base - (kOutOff >> shift));
        };
        asm volatile("mov.b32 %0, 0;" : "=r"(park_last));
#pragma unroll
        for (int k = 0; k < kPark * 8; k++) asm volatile("mov.b32 %0, 0;" : "=r"(park[k / 8][k % 8]));
#pragma unroll 1
        while (true) {
            mbar_wait(sb + kFullOff + 8 * s, ph);
            const int t = lds32(sb + kSlotOff + 4 * s);
            if (t >= num_tiles) break;
            const uint64_t desc = make_desc(sb + s * kStageBytes, 6144);
            my_turn();
            asm volatile("wgmma.fence.sync.aligned;" ::: "memory");
#pragma unroll
            for (int k = 0; k < 24; k++) {
                if (k == 19) pass_turn();
                wgmma_rs(acc, a[k], desc + desc_k(k), k != 0);
            }
            asm volatile("wgmma.commit_group.sync.aligned;" ::: "memory");
            asm volatile("wgmma.wait_group.sync.aligned 0;" ::: "memory");
            release_stage();
            const int keep = t >= park_from ? kPark + 1 : t >= mid_from && t < mid_to ? mid_n : 0;
            if (parked < keep) {
#pragma unroll
                for (int k = 0; k < kPark; k++)
                    if (parked == k) pack(park[k], acc);
                if (parked == kPark) {
                    uint32_t p[8];
                    pack(p, acc);
                    mbar_wait(sb + kPullBarOff, 0);
                    asm volatile("st.shared.v4.b32 [%0], {%1, %2, %3, %4};"
                                 ::"r"(spill_addr(0, 0, 0)), "r"(p[0]), "r"(p[1]), "r"(p[2]), "r"(p[3]) : "memory");
                    asm volatile("st.shared.v2.b32 [%0], {%1, %2};" ::"r"(spill_addr(6144, 1, t >> 24)), "r"(p[4]), "r"(p[5]) : "memory");
                    sts32(spill_addr(9216, 2, t >> 24), p[6]);
                    asm volatile("xor.b32 %0, %1, %2;" : "=r"(park_last) : "r"(p[7]), "r"(st_off));
                }
                if (threadIdx.x == 0) sts32(sb + kPSlotOff + 4 * parked, t);
                parked++;
            } else {
                uint32_t p[8];
                pack(p, acc);
                put(p, t);
                if (parked > keep) {
#pragma unroll
                    for (int k = 2; k >= 0; k--)
                        if (k < parked) put(park[k], threadIdx.x == 0 ? lds32(sb + kPSlotOff + 4 * k) : 0);
                    parked = 0;
                }
            }
        }
#pragma unroll
        for (int k = 0; k < kPark; k++)
            if (k < parked) put(park[k], threadIdx.x == 0 ? lds32(sb + kPSlotOff + 4 * k) : 0);
        if (parked > kPark) {
            uint32_t p[8];
            asm volatile("ld.shared.v4.b32 {%0, %1, %2, %3}, [%4];"
                         : "=r"(p[0]), "=r"(p[1]), "=r"(p[2]), "=r"(p[3]) : "r"(spill_addr(0, 0, 0)) : "memory");
            asm volatile("ld.shared.v2.b32 {%0, %1}, [%2];" : "=r"(p[4]), "=r"(p[5]) : "r"(spill_addr(6144, 1, parked >> 24)) : "memory");
            p[6] = lds32(spill_addr(9216, 2, parked >> 24));
            asm volatile("xor.b32 %0, %1, %2;" : "=r"(p[7]) : "r"(park_last), "r"(st_off));
            put(p, threadIdx.x == 0 ? lds32(sb + kPSlotOff + 4 * kPark) : 0);
        }
        mbar_wait(sb + kPullBarOff, 0);
        mbar_wait(sb + kOEmptyOff + 8 * ob, oph);
        if (threadIdx.x == 0) sts32(sb + kOSlotOff + 4 * ob, num_tiles);
        __syncwarp();
        if (lane == 0) mbar_arrive(sb + kOFullOff + 8 * ob);
    } else {
        asm volatile("setmaxnreg.dec.sync.aligned.u32 32;");
        const int role = __shfl_sync(0xffffffffu, (threadIdx.x >> 5) & 3, 0);
        const bool lead = (threadIdx.x & 31) == 0;
        if (role >= 2) {
            if (lead) {
                if (role == 2) {
#pragma unroll
                    for (int b = 0; b < kOutBufs; b++) {
                        mbar_init(sb + kOFullOff + 8 * b, 12);
                        mbar_init(sb + kOEmptyOff + 8 * b, 1);
                    }
                } else {
#pragma unroll
                    for (int s = 0; s < kStages; s++) {
                        mbar_init(sb + kFullOff + 8 * s, 1);
                        mbar_init(sb + kEmptyOff + 8 * s, 24);
                        if (s < 2) mbar_arrive(sb + kFullOff + 8 * s);
                    }
                    prefetch_map(&tm_x);
                    prefetch_map(&tm_o);
                }
                asm volatile("fence.mbarrier_init.release.cluster;" ::: "memory");
            }
            cluster_arrive();
            cluster_wait();
            if (role == 2) {
                uint64_t normal, streaming;
                asm volatile("createpolicy.fractional.L2::evict_normal.b64 %0, 1.0;" : "=l"(normal));
                asm volatile("createpolicy.fractional.L2::evict_first.b64 %0, 1.0;" : "=l"(streaming));
                int head = 0, tail = 0, freed = 0, n = 0, held = 0, pos = 0, k = 0, hold = 0, next = 0;
                uint32_t ph = 0;
                auto issue = [&](int u) {
                    if (lead) {
                        asm volatile("cp.async.bulk.tensor.3d.global.shared::cta.bulk_group.L2::cache_hint [%0, {%2, %3, %4}], [%1], %5;"
                                     ::"l"(&tm_o), "r"(sb + kOutOff + tail * kOutBytes), "r"(0), "r"((int)rank * 3),
                                       "r"(u * kTilePx), "l"(pos >= stream_from ? streaming : normal) : "memory");
                        asm volatile("cp.async.bulk.commit_group;" ::: "memory");
                    }
                    tail = (tail + 1) & (kOutBufs - 1);
                    held--;
                    n++;
                };
#pragma unroll 1
                while (true) {
                    const bool push = held > 0 && held >= hold;
                    const int oldest = __shfl_sync(0xffffffffu, lds32(sb + kOSlotOff + 4 * tail), 0);
                    mbar_wait(sb + kOFullOff + 8 * head, ph);
                    if (push) issue(oldest);
                    const int t = __shfl_sync(0xffffffffu, lds32(sb + kOSlotOff + 4 * head), 0);
                    int lag = 0;
                    if (t < num_tiles) {
                        held++;
                        pos = max(pos, t);
                        if (++head == kOutBufs) { head = 0; ph ^= 1; }
#pragma unroll 1
                        while (pos >= next) {
                            hold = kn.hold[k++];
                            next = k < kHoldPts ? kn.hold_pos[k] : 0x7fffffff;
                        }
                        lag = hold < 6 ? kn.lag : 0;
                    } else {
                        hold = 0;
                    }
#pragma unroll 1
                    while (held > hold) issue(lds32(sb + kOSlotOff + 4 * tail));
#pragma unroll 1
                    for (; n > lag; n--) {
                        if (lead) {
                            if (n == 1) asm volatile("cp.async.bulk.wait_group.read 0;" ::: "memory");
                            else if (n == 2) asm volatile("cp.async.bulk.wait_group.read 1;" ::: "memory");
                            else if (n <= 4) asm volatile("cp.async.bulk.wait_group.read 2;" ::: "memory");
                            else asm volatile("cp.async.bulk.wait_group.read 4;" ::: "memory");
                            mbar_arrive(sb + kOEmptyOff + 8 * freed);
                        }
                        freed = (freed + 1) & (kOutBufs - 1);
                    }
                    if (t >= num_tiles) break;
                }
            }
        } else if (role == 1) {
            const uint32_t t_start = __shfl_sync(0xffffffffu, globaltimer(), 0);
            const uint32_t my_slot = sb + kSlotOff + 4 * min(threadIdx.x & 31, kStages - 1);
            sts32(my_slot, 0);
            __threadfence_block();
            cluster_arrive();
            int k = 0;
#pragma unroll 1
            for (int t = blockIdx.x + gridDim.x; t < num_tiles; t += gridDim.x) {
                if (t < kn.pf_from) continue;
                const uint32_t due = kn.pf_t0 + (t - gridDim.x) * kn.pf_dt / gridDim.x;
                for (int n = 0; globaltimer() - t_start < due && n < 4096; n++) __nanosleep(50);
#pragma unroll 1
                while (k + 1 < kLeadPts && t >= kn.lead_pos[k + 1]) k++;
                const int max_lead = kn.lead[k] + ((t - kn.lead_pos[k]) * kn.lead_slope[k] >> 16);
                for (int n = 0; t > max_lead && n < 4096; n++) {
                    const int front = __reduce_max_sync(0xffffffffu, lds32_volatile(my_slot));
                    if (t - max_lead <= front || front >= num_tiles) break;
                    __nanosleep(50);
                }
                if (lead)
                    asm volatile("cp.async.bulk.prefetch.L2.global [%0], %1;"
                                 ::"l"((const char*)x + (size_t)t * kStageBytes), "r"(kStageBytes) : "memory");
            }
            cluster_wait();
        } else {
            const uint32_t t_start = __shfl_sync(0xffffffffu, globaltimer(), 0);
            if (lead) {
                mbar_init(sb + kPullBarOff, 1);
                asm volatile("fence.proxy.async.shared::cta;" ::: "memory");
                mbar_expect_tx(sb + kPullBarOff, rank * 3072 * kn.pull_n);
            }
            __threadfence_block();
            cluster_arrive();
            if (__shfl_sync(0xffffffffu, rank, 0) == 1) {
#pragma unroll 1
                for (int i = 0; i < kn.pull_n; i++) {
                    const uint32_t due = kn.pull_t0 + (i * gridDim.x + blockIdx.x) * kn.pull_dt / gridDim.x;
                    for (int n = 0; globaltimer() - t_start < due && n < 4096; n++) {}
                    if (lead)
                        asm volatile("cp.async.bulk.tensor.2d.shared::cluster.global.mbarrier::complete_tx::bytes [%0], [%1, {%3, %4}], [%2];"
                                     ::"r"(sb + kScratchOff), "l"(&tm_pull), "r"(sb + kPullBarOff), "r"(0),
                                       "r"(static_tile(i + 2) * 192) : "memory");
                }
            }
            cluster_wait();
            if (__shfl_sync(0xffffffffu, rank, 0) == 0) {
                const uint32_t peer = map_to_cta(sb, 1);
                const int nstatic = static_tiles * (gridDim.x >> 1);
                const unsigned last_fetch = num_tiles - nstatic + gridDim.x - 1;
                mbar_wait(sb + kEmptyOff, 0);
                mbar_wait(sb + kEmptyOff + 8, 0);
                int s = 2, g = 0, gap = 0, gap_next = 0;
                uint32_t earliest = 0;
                uint32_t ph = 0;
                auto fetch = [&](unsigned& raw) {
                    if (lead) asm volatile("atom.global.inc.u32 %0, [%1], %2;" : "=r"(raw) : "l"(&g_tile_counter), "r"(last_fetch) : "memory");
                };
                auto load = [&](int t, bool valid) {
                    mbar_wait(sb + kEmptyOff + 8 * s, ph);
                    __syncwarp();
                    if (gap) {
                        uint32_t now = globaltimer() - t_start;
                        for (int n = 0; now < earliest && n < 4096; n++) now = globaltimer() - t_start;
                        earliest = max(earliest, now - kn.slack) + gap;
                    }
                    const uint32_t full = kFullOff + 8 * s, slot = kSlotOff + 4 * s;
                    const uint32_t bytes = valid ? kStageBytes : 0;
                    if (lead && valid)
                        asm volatile(
                            "cp.async.bulk.tensor.4d.shared::cluster.global.mbarrier::complete_tx::bytes.multicast::cluster "
                            "[%0], [%1, {%3, %3, %3, %4}], [%2], %5;"
                            ::"r"(sb + s * kStageBytes), "l"(&tm_x), "r"(sb + full), "r"(0), "r"(t * (kTilePx / 8)),
                              "h"((uint16_t)3) : "memory");
                    if (lead) {
                        sts32(sb + slot, t);
                        mbar_expect_tx(sb + full, bytes);
                        asm volatile("mbarrier.arrive.expect_tx.shared::cluster.b64 _, [%0], %1;" ::"r"(peer + full), "r"(bytes + 4) : "memory");
                        asm volatile("st.async.weak.shared::cluster.mbarrier::complete_tx::bytes.b32 [%0], %1, [%2];"
                                     ::"r"(peer + slot), "r"(t), "r"(peer + full) : "memory");
                    }
                    if (++s == kStages) { s = 0; ph ^= 1; }
#pragma unroll 1
                    while (t >= gap_next) {
                        gap = kn.gap[g++];
                        gap_next = g < kGapPts ? kn.gap_pos[g] : 0x7fffffff;
                    }
                };
                unsigned raw0 = 0, raw1 = 0;
#pragma unroll 1
                for (int i = 2; i < static_tiles; i++) {
                    if (i == static_tiles - 2) fetch(raw0);
                    if (i == static_tiles - 1) fetch(raw1);
                    load(static_tile(i), true);
                }
                auto step = [&](unsigned& raw) -> bool {
                    const int t = nstatic + __shfl_sync(0xffffffffu, raw, 0);
                    const bool valid = t < num_tiles;
                    if (valid) fetch(raw);
                    load(t, valid);
                    return valid;
                };
#pragma unroll 1
                while (step(raw0) && step(raw1)) {}
#pragma unroll 1
                for (int k = 1; k < kStages; k++) {
                    mbar_wait(sb + kEmptyOff + 8 * s, ph);
                    if (++s == kStages) { s = 0; ph ^= 1; }
                }
            }
        }
    }
}

typedef CUresult (*EncodeTiledFn)(CUtensorMap*, CUtensorMapDataType, cuuint32_t, void*, const cuuint64_t*,
                                  const cuuint64_t*, const cuuint32_t*, const cuuint32_t*, CUtensorMapInterleave,
                                  CUtensorMapSwizzle, CUtensorMapL2promotion, CUtensorMapFloatOOBfill);

}

extern "C" void kernel_launch(void* const* d_in, const int* in_sizes, int n_in, void* d_out, int out_size) {
    (void)n_in; (void)out_size;
    const __nv_bfloat16* x = (const __nv_bfloat16*)d_in[0];
    const __nv_bfloat16* dw = (const __nv_bfloat16*)d_in[1];
    const __nv_bfloat16* pw = (const __nv_bfloat16*)d_in[2];
    const int pixels = in_sizes[0] / kC;

    static EncodeTiledFn encode = nullptr;
    static int grid = 0;
    if (!encode) {
        void* fn = nullptr;
        cudaDriverEntryPointQueryResult qr;
        cudaGetDriverEntryPoint("cuTensorMapEncodeTiled", &fn, cudaEnableDefault, &qr);
        encode = (EncodeTiledFn)fn;
        cudaFuncSetAttribute(dwsep_kernel, cudaFuncAttributeMaxDynamicSharedMemorySize, kSmemBytes);
        int sms = 0, clusters = 0;
        cudaDeviceGetAttribute(&sms, cudaDevAttrMultiProcessorCount, 0);
        cudaLaunchConfig_t cfg = {};
        cudaLaunchAttribute attr = {};
        attr.id = cudaLaunchAttributeClusterDimension;
        attr.val.clusterDim.x = 2;
        attr.val.clusterDim.y = attr.val.clusterDim.z = 1;
        cfg.gridDim = dim3(sms & ~1);
        cfg.blockDim = dim3(kThreads);
        cfg.dynamicSmemBytes = kSmemBytes;
        cfg.attrs = &attr;
        cfg.numAttrs = 1;
        if (cudaOccupancyMaxActiveClusters(&clusters, dwsep_kernel, &cfg) != cudaSuccess || clusters < 1) {
            (void)cudaGetLastError();
            clusters = sms / 2;
        }
        grid = 2 * (clusters < sms / 2 ? clusters : sms / 2);
    }

    CUtensorMap tm_w, tm_x0, tm_x, tm_o, tm_pull;
    auto make_map = [&](CUtensorMap* m, const void* base, int rank, const cuuint64_t* dims, const cuuint64_t* strides,
                        const cuuint32_t* box, CUtensorMapL2promotion promo) {
        const cuuint32_t ones[4] = {1, 1, 1, 1};
        encode(m, CU_TENSOR_MAP_DATA_TYPE_BFLOAT16, rank, (void*)base, dims, strides, box, ones,
               CU_TENSOR_MAP_INTERLEAVE_NONE, CU_TENSOR_MAP_SWIZZLE_128B, promo, CU_TENSOR_MAP_FLOAT_OOB_FILL_NONE);
    };
    {
        const cuuint64_t dims[3] = {64, kC, 6}, strides[2] = {kC * 2, 128};
        const cuuint32_t box[3] = {64, 64, 3};
        make_map(&tm_w, pw, 3, dims, strides, box, CU_TENSOR_MAP_L2_PROMOTION_L2_128B);
    }
    {
        const cuuint64_t dims[4] = {64, 8, 6, (cuuint64_t)pixels / 8}, strides[3] = {kC * 2, 128, kC * 2 * 8};
        const cuuint32_t box0[4] = {64, 8, 2, 8}, box[4] = {64, 8, 6, kTilePx / 8};
        make_map(&tm_x0, x, 4, dims, strides, box0, CU_TENSOR_MAP_L2_PROMOTION_L2_128B);
        make_map(&tm_x, x, 4, dims, strides, box, CU_TENSOR_MAP_L2_PROMOTION_L2_128B);
    }
    {
        const cuuint64_t dims[3] = {64, 6, (cuuint64_t)pixels}, strides[2] = {128, kC * 2};
        const cuuint32_t box[3] = {64, 3, kTilePx};
        make_map(&tm_o, d_out, 3, dims, strides, box, CU_TENSOR_MAP_L2_PROMOTION_NONE);
    }
    {
        const cuuint64_t dims[2] = {64, (cuuint64_t)pixels * 6}, strides[1] = {128};
        const cuuint32_t box[2] = {8, 192}, ones[2] = {1, 1};
        encode(&tm_pull, CU_TENSOR_MAP_DATA_TYPE_BFLOAT16, 2, (void*)x, dims, strides, box, ones, CU_TENSOR_MAP_INTERLEAVE_NONE,
               CU_TENSOR_MAP_SWIZZLE_NONE, CU_TENSOR_MAP_L2_PROMOTION_L2_128B, CU_TENSOR_MAP_FLOAT_OOB_FILL_NONE);
    }
    Knobs kn = g_knobs;
    for (int k = 0; k < kLeadPts; k++)
        kn.lead_slope[k] = k < kLeadPts - 1 ? (kn.lead[k + 1] - kn.lead[k]) * 65536 / (kn.lead_pos[k + 1] - kn.lead_pos[k]) : 0;
    dwsep_kernel<<<grid, kThreads, kSmemBytes, cudaStreamPerThread>>>(tm_w, tm_x0, tm_x, tm_o, tm_pull, x, dw, pw,
                                                                      pixels / kTilePx, kn.mid_from, kn.mid_to, kn.mid_n,
                                                                      kn.park_from, kn.static_tiles, kn.stream_from, kn);
}
```

```cpp
#include <cuda_runtime.h>
#include <cuda_bf16.h>
#include <cuda.h>
#include <stdint.h>

namespace {

constexpr int kC = 384;
constexpr int kTilePx = 32;
constexpr int kStages = 5;
constexpr int kOutBufs = 8;
constexpr int kPark = 5;
constexpr int kThreads = 512;
constexpr int kStageBytes = kTilePx * kC * 2;
constexpr int kOutBytes = kTilePx * 192 * 2;
constexpr int kWChunkBytes = 64 * 192 * 2;
constexpr int kXSlabBytes = 64 * 128 * 2;
constexpr int kWOff = 3 * kStageBytes;
constexpr int kOutOff = kStages * kStageBytes;
constexpr int kSpillOff = kOutOff + kOutBufs * kOutBytes;
constexpr int kDwOff = kSpillOff;
constexpr int kScratchOff = kSpillOff + 1024;
constexpr int kFullOff = kSpillOff + 384 * 28;
constexpr int kEmptyOff = kFullOff + 8 * kStages;
constexpr int kOFullOff = kEmptyOff + 8 * kStages;
constexpr int kOEmptyOff = kOFullOff + 8 * kOutBufs;
constexpr int kWBarOff = kOEmptyOff + 8 * kOutBufs;
constexpr int kXBarOff = kWBarOff + 8 * 3;
constexpr int kDwBarOff = kXBarOff + 8 * 3;
constexpr int kPullBarOff = kDwBarOff + 8;
constexpr int kSlotOff = kPullBarOff + 8;
constexpr int kOSlotOff = kSlotOff + 4 * kStages;
constexpr int kPSlotOff = kOSlotOff + 4 * kOutBufs;
constexpr int kSmemBytes = kPSlotOff + 4 * (kPark + 1);
static_assert(kWChunkBytes == kStageBytes && kWOff + 6 * kWChunkBytes <= kDwOff, "weight staging");
static_assert(kSmemBytes <= 232448, "shared memory");

constexpr int kGapPts = 6, kHoldPts = 12, kLeadPts = 10;
struct Knobs {
    int first_gap;
    int pull_n, pull_t0, pull_dt;
    int pf_from, pf_t0, pf_dt;
    int static_tiles;
    int mid_from, mid_to, mid_n;
    int park_from;
    int stream_from;
    int lag;
    int slack;
    int gap_pos[kGapPts], gap[kGapPts];
    int hold_pos[kHoldPts], hold[kHoldPts];
    int lead_pos[kLeadPts], lead[kLeadPts];
    int lead_slope[kLeadPts];
};
#define DEFAULT_KNOBS {523, 5, 56, 356, 594, 229, 658, 20, 1590, 3283, 2, 3412, 4261, 2, 245, \
    {0, 300, 1899, 2489, 3243, 3969}, {0, 0, 873, 963, 806, 0}, \
    {0, 376, 454, 588, 603, 957, 962, 1914, 3000, 4242, 4378, 4608}, {0, 1, 2, 3, 4, 5, 6, 7, 7, 4, 2, 2}, \
    {0, 847, 1443, 2003, 2068, 2295, 3698, 3821, 3893, 4398}, {209, 370, 538, 332, 386, 327, 138, 198, 238, 158}}
constexpr Knobs g_knobs = DEFAULT_KNOBS;

__device__ unsigned int g_tile_counter;

__device__ __forceinline__ uint32_t smem_u32(const void* p) { return (uint32_t)__cvta_generic_to_shared(p); }

__device__ __forceinline__ void mbar_init(uint32_t bar, uint32_t cnt) {
    asm volatile("mbarrier.init.shared::cta.b64 [%0], %1;" ::"r"(bar), "r"(cnt) : "memory");
}
__device__ __forceinline__ void mbar_expect_tx(uint32_t bar, uint32_t bytes) {
    asm volatile("mbarrier.arrive.expect_tx.shared::cta.b64 _, [%0], %1;" ::"r"(bar), "r"(bytes) : "memory");
}
__device__ __forceinline__ void mbar_arrive(uint32_t bar) {
    asm volatile("mbarrier.arrive.shared::cta.b64 _, [%0];" ::"r"(bar) : "memory");
}
__device__ __forceinline__ void mbar_arrive_cluster(uint32_t bar) {
    asm volatile("mbarrier.arrive.shared::cluster.b64 _, [%0];" ::"r"(bar) : "memory");
}
__device__ __forceinline__ void mbar_wait(uint32_t bar, uint32_t parity) {
    asm volatile(
        "{\n.reg .pred p;\n.reg .u32 n;\n"
        "mbarrier.try_wait.parity.shared::cta.b64 p, [%0], %1;\n"
        "@p bra DONE;\n"
        "mov.u32 n, 0;\n"
        "LOOP:\n"
        "mbarrier.try_wait.parity.shared::cta.b64 p, [%0], %1;\n"
        "@p bra DONE;\n"
        "add.u32 n, n, 1;\n"
        "setp.lt.u32 p, n, 4194304;\n"
        "@p bra LOOP;\n"
        "trap;\n"
        "DONE:\n}" ::"r"(bar), "r"(parity) : "memory");
}
__device__ __forceinline__ uint32_t map_to_cta(uint32_t addr, uint32_t cta) {
    uint32_t r;
    asm("mapa.shared::cluster.u32 %0, %1, %2;" : "=r"(r) : "r"(addr), "r"(cta));
    return r;
}
__device__ __forceinline__ void named_bar_sync(int id, int n) { asm volatile("bar.sync %0, %1;" ::"r"(id), "r"(n) : "memory"); }
__device__ __forceinline__ void named_bar_arrive(int id, int n) { asm volatile("bar.arrive %0, %1;" ::"r"(id), "r"(n) : "memory"); }
__device__ __forceinline__ void cluster_arrive() {
    __syncwarp();
    asm volatile("barrier.cluster.arrive.relaxed.aligned;" ::: "memory");
}
__device__ __forceinline__ void cluster_wait() {
    __syncwarp();
    asm volatile("barrier.cluster.wait.acquire.aligned;" ::: "memory");
}
__device__ __forceinline__ void prefetch_line(const void* p) { asm volatile("prefetch.global.L2 [%0];" ::"l"(p) : "memory"); }
__device__ __forceinline__ void prefetch_map(const CUtensorMap* m) { asm volatile("prefetch.tensormap [%0];" ::"l"(m) : "memory"); }
__device__ __forceinline__ uint32_t globaltimer() {
    uint32_t t;
    asm volatile("mov.u32 %0, %%globaltimer_lo;" : "=r"(t));
    return t;
}
__device__ __forceinline__ uint32_t clock32() {
    uint32_t t;
    asm volatile("mov.u32 %0, %%clock;" : "=r"(t));
    return t;
}
__device__ __forceinline__ int lds32(uint32_t addr) {
    int v;
    asm volatile("ld.shared.b32 %0, [%1];" : "=r"(v) : "r"(addr) : "memory");
    return v;
}
__device__ __forceinline__ int lds32_volatile(uint32_t addr) {
    int v;
    asm volatile("ld.volatile.shared.b32 %0, [%1];" : "=r"(v) : "r"(addr) : "memory");
    return v;
}
__device__ __forceinline__ void sts32(uint32_t addr, int v) { asm volatile("st.shared.b32 [%0], %1;" ::"r"(addr), "r"(v) : "memory"); }

#define ACC4(o) "+f"(d[o]), "+f"(d[o + 1]), "+f"(d[o + 2]), "+f"(d[o + 3])
#define ACC16(o) ACC4(o), ACC4(o + 4), ACC4(o + 8), ACC4(o + 12)
__device__ __forceinline__ void wgmma_rs(float (&d)[32], const uint32_t (&a)[4], uint64_t desc_b, int scale_d) {
    asm volatile(
        "{\n.reg .pred p;\nsetp.ne.b32 p, %37, 0;\n"
        "wgmma.mma_async.sync.aligned.m64n64k16.f32.bf16.bf16 "
        "{%0, %1, %2, %3, %4, %5, %6, %7, %8, %9, %10, %11, %12, %13, %14, %15, "
        "%16, %17, %18, %19, %20, %21, %22, %23, %24, %25, %26, %27, %28, %29, %30, %31}, "
        "{%32, %33, %34, %35}, %36, p, 1, 1, 0;\n}"
        : ACC16(0), ACC16(16)
        : "r"(a[0]), "r"(a[1]), "r"(a[2]), "r"(a[3]), "l"(desc_b), "r"(scale_d));
}
__device__ __forceinline__ void wgmma_rs(float (&d)[16], const uint32_t (&a)[4], uint64_t desc_b, int scale_d) {
    asm volatile(
        "{\n.reg .pred p;\nsetp.ne.b32 p, %21, 0;\n"
        "wgmma.mma_async.sync.aligned.m64n32k16.f32.bf16.bf16 "
        "{%0, %1, %2, %3, %4, %5, %6, %7, %8, %9, %10, %11, %12, %13, %14, %15}, "
        "{%16, %17, %18, %19}, %20, p, 1, 1, 0;\n}"
        : ACC16(0)
        : "r"(a[0]), "r"(a[1]), "r"(a[2]), "r"(a[3]), "l"(desc_b), "r"(scale_d));
}
__device__ __forceinline__ uint64_t make_desc(uint32_t addr, uint32_t group_stride) {
    return (uint64_t(1) << 62) | (uint64_t(group_stride >> 4) << 32) | (uint64_t(1) << 16) | (uint64_t)((addr & 0x3FFFF) >> 4);
}
__device__ __forceinline__ constexpr uint64_t desc_k(int k) { return (uint64_t)(((k >> 2) * 1024 + (k & 3) * 32) >> 4); }

__device__ __forceinline__ uint32_t pack_bf16(float lo, float hi) {
    uint32_t r;
    asm("cvt.rn.bf16x2.f32 %0, %1, %2;" : "=r"(r) : "f"(hi), "f"(lo));
    return r;
}
__device__ __forceinline__ uint32_t mul_bf16x2(uint32_t a, uint32_t b) {
    uint32_t r;
    asm("mul.rn.bf16x2 %0, %1, %2;" : "=r"(r) : "r"(a), "r"(b));
    return r;
}

__global__ void __cluster_dims__(2, 1, 1) __launch_bounds__(kThreads, 1)
dwsep_kernel(const __grid_constant__ CUtensorMap tm_w, const __grid_constant__ CUtensorMap tm_x0,
             const __grid_constant__ CUtensorMap tm_x, const __grid_constant__ CUtensorMap tm_o,
             const __grid_constant__ CUtensorMap tm_pull,
             const __nv_bfloat16* __restrict__ x, const __nv_bfloat16* __restrict__ dw,
             const __nv_bfloat16* __restrict__ pw, int num_tiles,
             int mid_from, int mid_to, int mid_n, int park_from, int static_tiles, int stream_from,
             const __grid_constant__ Knobs kn) {
    extern __shared__ __align__(1024) uint8_t smem_raw[];
    const uint32_t sb = smem_u32(smem_raw);

    uint32_t rank;
    asm("mov.u32 %0, %%cluster_ctarank;" : "=r"(rank));
    const int cluster = blockIdx.x >> 1;
    auto static_tile = [&](int i) { return (i >> 1) * gridDim.x + cluster * 2 + (i & 1); };

    if (threadIdx.x < 32) {
        prefetch_line(threadIdx.x < 18 ? (const char*)pw + (blockIdx.x & 127) * 2304 + threadIdx.x * 128
                                       : (const char*)dw + min(threadIdx.x - 18, 5) * 128);
    } else if (threadIdx.x < 224) {
        const uint32_t c0 = __shfl_sync(0xffffffffu, clock32(), 0), chunk = (threadIdx.x >> 5) - 1;
        const uint32_t delay = ((chunk >> 1) * gridDim.x + blockIdx.x) * kn.first_gap >> 7;
        for (int n = 0; clock32() - c0 < delay && n < 1024; n++) {}
        prefetch_line((const char*)x + (size_t)blockIdx.x * kStageBytes + (threadIdx.x & 31) * 768 + chunk * 128);
    } else if (threadIdx.x == 288) {
        prefetch_map(&tm_w);
        prefetch_map(&tm_x0);
        if (rank == 1) prefetch_map(&tm_pull);
    }
    if (threadIdx.x >> 5 == 8) {
        if (threadIdx.x == 256) {
#pragma unroll
            for (int b = 0; b < 7; b++) mbar_init(sb + kWBarOff + 8 * b, 1);
            asm volatile("fence.proxy.async.shared::cta;" ::: "memory");
        }
        __syncwarp();
        named_bar_arrive(8, 384);
        if (threadIdx.x == 256) {
            mbar_expect_tx(sb + kDwBarOff, kC * 2);
            asm volatile("cp.async.bulk.shared::cluster.global.mbarrier::complete_tx::bytes [%0], [%1], %2, [%3];"
                         ::"r"(sb + kDwOff), "l"(dw), "r"(kC * 2), "r"(sb + kDwBarOff) : "memory");
#pragma unroll
            for (int j = 0; j < 3; j++) {
                mbar_expect_tx(sb + kWBarOff + 8 * j, 2 * kWChunkBytes);
#pragma unroll
                for (int c = 2 * j; c < 2 * j + 2; c++)
                    asm volatile("cp.async.bulk.tensor.3d.shared::cluster.global.mbarrier::complete_tx::bytes [%0], [%1, {%3, %4, %5}], [%2];"
                                 ::"r"(sb + kWOff + c * kWChunkBytes), "l"(&tm_w), "r"(sb + kWBarOff + 8 * j), "r"(0), "r"(c * 64),
                                   "r"((int)rank * 3) : "memory");
                mbar_expect_tx(sb + kXBarOff + 8 * j, kXSlabBytes);
                asm volatile("cp.async.bulk.tensor.4d.shared::cluster.global.mbarrier::complete_tx::bytes [%0], [%1, {%3, %3, %4, %5}], [%2];"
                             ::"r"(sb + j * kXSlabBytes), "l"(&tm_x0), "r"(sb + kXBarOff + 8 * j), "r"(0), "r"(2 * j),
                               "r"(cluster * 8) : "memory");
            }
        }
        __syncwarp();
    }

    if (threadIdx.x < 384) {
        asm volatile("setmaxnreg.inc.sync.aligned.u32 160;");
        cluster_arrive();
        if (threadIdx.x >> 5 != 8) named_bar_sync(8, 384);
        const int wg = __shfl_sync(0xffffffffu, threadIdx.x >> 7, 0);
        const int warp = (threadIdx.x >> 5) & 3;
        const int lane = threadIdx.x & 31;
        const int mi = lane >> 3, ri = lane & 7;
        const uint32_t leader_empty = map_to_cta(sb + kEmptyOff, 0);
        uint32_t st_off = sb + kOutOff + (((mi >> 1) * 8 + ri) * 3 + wg) * 128 + (((2 * warp + (mi & 1)) ^ ((3 * ri + wg) & 7)) << 4);
        int s = 0, ob = 0;
        uint32_t ph = 0, oph = 1;
        auto release_stage = [&]() {
            if (lane == 0) mbar_arrive_cluster(leader_empty + 8 * s);
            if (++s == kStages) { s = 0; ph ^= 1; }
        };
        auto pack = [&](uint32_t (&p)[8], const float* acc) {
#pragma unroll
            for (int k = 0; k < 8; k++) p[k] = pack_bf16(acc[2 * k], acc[2 * k + 1]);
        };
        auto put = [&](const uint32_t (&p)[8], int t) {
            mbar_wait(sb + kOEmptyOff + 8 * ob, oph);
            if (threadIdx.x == 0) sts32(sb + kOSlotOff + 4 * ob, t);
#pragma unroll
            for (int q = 0; q < 2; q++)
                asm volatile("stmatrix.sync.aligned.m8n8.x4.trans.shared.b16 [%0], {%1, %2, %3, %4};"
                             ::"r"(st_off + ob * kOutBytes + q * (16 * 384)), "r"(p[4 * q]), "r"(p[4 * q + 1]),
                               "r"(p[4 * q + 2]), "r"(p[4 * q + 3]) : "memory");
            asm volatile("fence.proxy.async.shared::cta;" ::: "memory");
            __syncwarp();
            if (lane == 0) mbar_arrive(sb + kOFullOff + 8 * ob);
            if (++ob == kOutBufs) { ob = 0; oph ^= 1; }
        };
        auto my_turn = [&]() { named_bar_sync(2 + wg, 256); };
        auto pass_turn = [&]() { named_bar_arrive(wg == 2 ? 2 : 3 + wg, 256); };
        if (wg == 2) pass_turn();

        uint32_t a[24][4];
        {
            float acc0[32];
            uint32_t dws[48];
            mbar_wait(sb + kDwBarOff, 0);
#pragma unroll
            for (int k = 0; k < 48; k++) dws[k] = lds32(sb + kDwOff + k * 16 + (lane & 3) * 4);
            cluster_wait();
            if (lane < 3) mbar_arrive_cluster(leader_empty + 8 * lane);
            const uint32_t wbase = sb + kWOff + wg * 8192 + ((mi >> 1) * 8 + ri) * 128 + (((2 * warp + (mi & 1)) ^ ri) << 4);
            const uint64_t desc = make_desc(sb, 2048);
#pragma unroll
            for (int j = 0; j < 3; j++) {
                mbar_wait(sb + kWBarOff + 8 * j, 0);
#pragma unroll
                for (int k = 8 * j; k < 8 * j + 8; k++) {
                    asm volatile("ldmatrix.sync.aligned.m8n8.x4.trans.shared.b16 {%0, %1, %2, %3}, [%4];"
                                 : "=r"(a[k][0]), "=r"(a[k][1]), "=r"(a[k][2]), "=r"(a[k][3])
                                 : "r"(wbase + (k >> 2) * kWChunkBytes + (k & 3) * 2048) : "memory");
                    a[k][0] = mul_bf16x2(a[k][0], dws[2 * k]);
                    a[k][1] = mul_bf16x2(a[k][1], dws[2 * k]);
                    a[k][2] = mul_bf16x2(a[k][2], dws[2 * k + 1]);
                    a[k][3] = mul_bf16x2(a[k][3], dws[2 * k + 1]);
                }
                uint32_t dep = 0;
#pragma unroll
                for (int k = 8 * j; k < 8 * j + 8; k++) dep ^= a[k][3];
                dep &= num_tiles >> 24;
                if (j == 0 && lane >= 3 && lane < kStages) mbar_arrive_cluster(leader_empty + 8 * lane + dep);
                if (j == 2) {
                    named_bar_arrive((wg == 0 ? 6 : 5) + dep, 384);
                    named_bar_arrive(wg == 2 ? 6 : 7, 384);
                }
                mbar_wait(sb + kXBarOff + 8 * j, 0);
                my_turn();
                asm volatile("wgmma.fence.sync.aligned;" ::: "memory");
#pragma unroll
                for (int k = 0; k < 8; k++) wgmma_rs(acc0, a[8 * j + k], desc + (j * kXSlabBytes >> 4) + desc_k(k), j + k != 0);
                pass_turn();
            }
            asm volatile("wgmma.commit_group.sync.aligned;" ::: "memory");
            named_bar_sync(5 + wg, 384);
            asm volatile("wgmma.wait_group.sync.aligned 0;" ::: "memory");
            release_stage();
            release_stage();
            uint32_t p[8];
            pack(p, acc0);
            put(p, static_tile(0));
            pack(p, acc0 + 16);
            put(p, static_tile(1));
        }

        float acc[16];
        uint32_t park[kPark][8], park_last;
        int parked = 0;
        st_off += num_tiles >> 24;
        auto spill_addr = [&](int base, int shift, int zero) {
            return ((st_off + zero) >> shift) + (sb - (sb >> shift) + kSpillOff + base - (kOutOff >> shift));
        };
        asm volatile("mov.b32 %0, 0;" : "=r"(park_last));
#pragma unroll
        for (int k = 0; k < kPark * 8; k++) asm volatile("mov.b32 %0, 0;" : "=r"(park[k / 8][k % 8]));
#pragma unroll 1
        while (true) {
            mbar_wait(sb + kFullOff + 8 * s, ph);
            const int t = lds32(sb + kSlotOff + 4 * s);
            if (t >= num_tiles) break;
            const uint64_t desc = make_desc(sb + s * kStageBytes, 6144);
            my_turn();
            asm volatile("wgmma.fence.sync.aligned;" ::: "memory");
#pragma unroll
            for (int k = 0; k < 24; k++) {
                if (k == 19) pass_turn();
                wgmma_rs(acc, a[k], desc + desc_k(k), k != 0);
            }
            asm volatile("wgmma.commit_group.sync.aligned;" ::: "memory");
            asm volatile("wgmma.wait_group.sync.aligned 0;" ::: "memory");
            release_stage();
            const int keep = t >= park_from ? kPark + 1 : t >= mid_from && t < mid_to ? mid_n : 0;
            if (parked < keep) {
#pragma unroll
                for (int k = 0; k < kPark; k++)
                    if (parked == k) pack(park[k], acc);
                if (parked == kPark) {
                    uint32_t p[8];
                    pack(p, acc);
                    mbar_wait(sb + kPullBarOff, 0);
                    asm volatile("st.shared.v4.b32 [%0], {%1, %2, %3, %4};"
                                 ::"r"(spill_addr(0, 0, 0)), "r"(p[0]), "r"(p[1]), "r"(p[2]), "r"(p[3]) : "memory");
                    asm volatile("st.shared.v2.b32 [%0], {%1, %2};" ::"r"(spill_addr(6144, 1, t >> 24)), "r"(p[4]), "r"(p[5]) : "memory");
                    sts32(spill_addr(9216, 2, t >> 24), p[6]);
                    asm volatile("xor.b32 %0, %1, %2;" : "=r"(park_last) : "r"(p[7]), "r"(st_off));
                }
                if (threadIdx.x == 0) sts32(sb + kPSlotOff + 4 * parked, t);
                parked++;
            } else {
                uint32_t p[8];
                pack(p, acc);
                put(p, t);
                if (parked > keep) {
#pragma unroll
                    for (int k = 2; k >= 0; k--)
                        if (k < parked) put(park[k], threadIdx.x == 0 ? lds32(sb + kPSlotOff + 4 * k) : 0);
                    parked = 0;
                }
            }
        }
#pragma unroll
        for (int k = 0; k < kPark; k++)
            if (k < parked) put(park[k], threadIdx.x == 0 ? lds32(sb + kPSlotOff + 4 * k) : 0);
        if (parked > kPark) {
            uint32_t p[8];
            asm volatile("ld.shared.v4.b32 {%0, %1, %2, %3}, [%4];"
                         : "=r"(p[0]), "=r"(p[1]), "=r"(p[2]), "=r"(p[3]) : "r"(spill_addr(0, 0, 0)) : "memory");
            asm volatile("ld.shared.v2.b32 {%0, %1}, [%2];" : "=r"(p[4]), "=r"(p[5]) : "r"(spill_addr(6144, 1, parked >> 24)) : "memory");
            p[6] = lds32(spill_addr(9216, 2, parked >> 24));
            asm volatile("xor.b32 %0, %1, %2;" : "=r"(p[7]) : "r"(park_last), "r"(st_off));
            put(p, threadIdx.x == 0 ? lds32(sb + kPSlotOff + 4 * kPark) : 0);
        }
        mbar_wait(sb + kPullBarOff, 0);
        mbar_wait(sb + kOEmptyOff + 8 * ob, oph);
        if (threadIdx.x == 0) sts32(sb + kOSlotOff + 4 * ob, num_tiles);
        __syncwarp();
        if (lane == 0) mbar_arrive(sb + kOFullOff + 8 * ob);
    } else {
        asm volatile("setmaxnreg.dec.sync.aligned.u32 32;");
        const int role = __shfl_sync(0xffffffffu, (threadIdx.x >> 5) & 3, 0);
        const bool lead = (threadIdx.x & 31) == 0;
        if (role >= 2) {
            if (lead) {
                if (role == 2) {
#pragma unroll
                    for (int b = 0; b < kOutBufs; b++) {
                        mbar_init(sb + kOFullOff + 8 * b, 12);
                        mbar_init(sb + kOEmptyOff + 8 * b, 1);
                    }
                } else {
#pragma unroll
                    for (int s = 0; s < kStages; s++) {
                        mbar_init(sb + kFullOff + 8 * s, 1);
                        mbar_init(sb + kEmptyOff + 8 * s, 24);
                        if (s < 2) mbar_arrive(sb + kFullOff + 8 * s);
                    }
                    prefetch_map(&tm_x);
                    prefetch_map(&tm_o);
                }
                asm volatile("fence.mbarrier_init.release.cluster;" ::: "memory");
            }
            cluster_arrive();
            cluster_wait();
            if (role == 2) {
                uint64_t normal, streaming;
                asm volatile("createpolicy.fractional.L2::evict_normal.b64 %0, 1.0;" : "=l"(normal));
                asm volatile("createpolicy.fractional.L2::evict_first.b64 %0, 1.0;" : "=l"(streaming));
                int head = 0, tail = 0, freed = 0, n = 0, held = 0, pos = 0, k = 0, hold = 0, next = 0;
                uint32_t ph = 0;
                auto issue = [&](int u) {
                    if (lead) {
                        asm volatile("cp.async.bulk.tensor.3d.global.shared::cta.bulk_group.L2::cache_hint [%0, {%2, %3, %4}], [%1], %5;"
                                     ::"l"(&tm_o), "r"(sb + kOutOff + tail * kOutBytes), "r"(0), "r"((int)rank * 3),
                                       "r"(u * kTilePx), "l"(pos >= stream_from ? streaming : normal) : "memory");
                        asm volatile("cp.async.bulk.commit_group;" ::: "memory");
                    }
                    tail = (tail + 1) & (kOutBufs - 1);
                    held--;
                    n++;
                };
#pragma unroll 1
                while (true) {
                    const bool push = held > 0 && held >= hold;
                    const int oldest = __shfl_sync(0xffffffffu, lds32(sb + kOSlotOff + 4 * tail), 0);
                    mbar_wait(sb + kOFullOff + 8 * head, ph);
                    if (push) issue(oldest);
                    const int t = __shfl_sync(0xffffffffu, lds32(sb + kOSlotOff + 4 * head), 0);
                    int lag = 0;
                    if (t < num_tiles) {
                        held++;
                        pos = max(pos, t);
                        if (++head == kOutBufs) { head = 0; ph ^= 1; }
#pragma unroll 1
                        while (pos >= next) {
                            hold = kn.hold[k++];
                            next = k < kHoldPts ? kn.hold_pos[k] : 0x7fffffff;
                        }
                        lag = hold < 6 ? kn.lag : 0;
                    } else {
                        hold = 0;
                    }
#pragma unroll 1
                    while (held > hold) issue(lds32(sb + kOSlotOff + 4 * tail));
#pragma unroll 1
                    for (; n > lag; n--) {
                        if (lead) {
                            if (n == 1) asm volatile("cp.async.bulk.wait_group.read 0;" ::: "memory");
                            else if (n == 2) asm volatile("cp.async.bulk.wait_group.read 1;" ::: "memory");
                            else if (n <= 4) asm volatile("cp.async.bulk.wait_group.read 2;" ::: "memory");
                            else asm volatile("cp.async.bulk.wait_group.read 4;" ::: "memory");
                            mbar_arrive(sb + kOEmptyOff + 8 * freed);
                        }
                        freed = (freed + 1) & (kOutBufs - 1);
                    }
                    if (t >= num_tiles) break;
                }
            }
        } else if (role == 1) {
            const uint32_t t_start = __shfl_sync(0xffffffffu, globaltimer(), 0);
            const uint32_t my_slot = sb + kSlotOff + 4 * min(threadIdx.x & 31, kStages - 1);
            sts32(my_slot, 0);
            __threadfence_block();
            cluster_arrive();
            int k = 0;
#pragma unroll 1
            for (int t = blockIdx.x + gridDim.x; t < num_tiles; t += gridDim.x) {
                if (t < kn.pf_from) continue;
                const uint32_t due = kn.pf_t0 + (t - gridDim.x) * kn.pf_dt / gridDim.x;
                for (int n = 0; globaltimer() - t_start < due && n < 4096; n++) __nanosleep(50);
#pragma unroll 1
                while (k + 1 < kLeadPts && t >= kn.lead_pos[k + 1]) k++;
                const int max_lead = kn.lead[k] + ((t - kn.lead_pos[k]) * kn.lead_slope[k] >> 16);
                for (int n = 0; t > max_lead && n < 4096; n++) {
                    const int front = __reduce_max_sync(0xffffffffu, lds32_volatile(my_slot));
                    if (t - max_lead <= front || front >= num_tiles) break;
                    __nanosleep(50);
                }
                if (lead)
                    asm volatile("cp.async.bulk.prefetch.L2.global [%0], %1;"
                                 ::"l"((const char*)x + (size_t)t * kStageBytes), "r"(kStageBytes) : "memory");
            }
            cluster_wait();
        } else {
            const uint32_t t_start = __shfl_sync(0xffffffffu, globaltimer(), 0);
            if (lead) {
                mbar_init(sb + kPullBarOff, 1);
                asm volatile("fence.proxy.async.shared::cta;" ::: "memory");
                mbar_expect_tx(sb + kPullBarOff, rank * 3072 * kn.pull_n);
            }
            __threadfence_block();
            cluster_arrive();
            if (__shfl_sync(0xffffffffu, rank, 0) == 1) {
#pragma unroll 1
                for (int i = 0; i < kn.pull_n; i++) {
                    const uint32_t due = kn.pull_t0 + (i * gridDim.x + blockIdx.x) * kn.pull_dt / gridDim.x;
                    for (int n = 0; globaltimer() - t_start < due && n < 4096; n++) {}
                    if (lead)
                        asm volatile("cp.async.bulk.tensor.2d.shared::cluster.global.mbarrier::complete_tx::bytes [%0], [%1, {%3, %4}], [%2];"
                                     ::"r"(sb + kScratchOff), "l"(&tm_pull), "r"(sb + kPullBarOff), "r"(0),
                                       "r"(static_tile(i + 2) * 192) : "memory");
                }
            }
            cluster_wait();
            if (__shfl_sync(0xffffffffu, rank, 0) == 0) {
                const uint32_t peer = map_to_cta(sb, 1);
                const int nstatic = static_tiles * (gridDim.x >> 1);
                const unsigned last_fetch = num_tiles - nstatic + gridDim.x - 1;
                mbar_wait(sb + kEmptyOff, 0);
                mbar_wait(sb + kEmptyOff + 8, 0);
                int s = 2, g = 0, gap = 0, gap_next = 0;
                uint32_t earliest = 0;
                uint32_t ph = 0;
                auto fetch = [&](unsigned& raw) {
                    if (lead) asm volatile("atom.global.inc.u32 %0, [%1], %2;" : "=r"(raw) : "l"(&g_tile_counter), "r"(last_fetch) : "memory");
                };
                auto load = [&](int t, bool valid) {
                    mbar_wait(sb + kEmptyOff + 8 * s, ph);
                    __syncwarp();
                    if (gap) {
                        uint32_t now = globaltimer() - t_start;
                        for (int n = 0; now < earliest && n < 4096; n++) now = globaltimer() - t_start;
                        earliest = max(earliest, now - kn.slack) + gap;
                    }
                    const uint32_t full = kFullOff + 8 * s, slot = kSlotOff + 4 * s;
                    const uint32_t bytes = valid ? kStageBytes : 0;
                    if (lead && valid)
                        asm volatile(
                            "cp.async.bulk.tensor.4d.shared::cluster.global.mbarrier::complete_tx::bytes.multicast::cluster "
                            "[%0], [%1, {%3, %3, %3, %4}], [%2], %5;"
                            ::"r"(sb + s * kStageBytes), "l"(&tm_x), "r"(sb + full), "r"(0), "r"(t * (kTilePx / 8)),
                              "h"((uint16_t)3) : "memory");
                    if (lead) {
                        sts32(sb + slot, t);
                        mbar_expect_tx(sb + full, bytes);
                        asm volatile("mbarrier.arrive.expect_tx.shared::cluster.b64 _, [%0], %1;" ::"r"(peer + full), "r"(bytes + 4) : "memory");
                        asm volatile("st.async.weak.shared::cluster.mbarrier::complete_tx::bytes.b32 [%0], %1, [%2];"
                                     ::"r"(peer + slot), "r"(t), "r"(peer + full) : "memory");
                    }
                    if (++s == kStages) { s = 0; ph ^= 1; }
#pragma unroll 1
                    while (t >= gap_next) {
                        gap = kn.gap[g++];
                        gap_next = g < kGapPts ? kn.gap_pos[g] : 0x7fffffff;
                    }
                };
                unsigned raw0 = 0, raw1 = 0;
#pragma unroll 1
                for (int i = 2; i < static_tiles; i++) {
                    if (i == static_tiles - 2) fetch(raw0);
                    if (i == static_tiles - 1) fetch(raw1);
                    load(static_tile(i), true);
                }
                auto step = [&](unsigned& raw) -> bool {
                    const int t = nstatic + __shfl_sync(0xffffffffu, raw, 0);
                    const bool valid = t < num_tiles;
                    if (valid) fetch(raw);
                    load(t, valid);
                    return valid;
                };
#pragma unroll 1
                while (step(raw0) && step(raw1)) {}
#pragma unroll 1
                for (int k = 1; k < kStages; k++) {
                    mbar_wait(sb + kEmptyOff + 8 * s, ph);
                    if (++s == kStages) { s = 0; ph ^= 1; }
                }
            }
        }
    }
}

typedef CUresult (*EncodeTiledFn)(CUtensorMap*, CUtensorMapDataType, cuuint32_t, void*, const cuuint64_t*,
                                  const cuuint64_t*, const cuuint32_t*, const cuuint32_t*, CUtensorMapInterleave,
                                  CUtensorMapSwizzle, CUtensorMapL2promotion, CUtensorMapFloatOOBfill);

}

extern "C" void kernel_launch(void* const* d_in, const int* in_sizes, int n_in, void* d_out, int out_size) {
    (void)n_in; (void)out_size;
    const __nv_bfloat16* x = (const __nv_bfloat16*)d_in[0];
    const __nv_bfloat16* dw = (const __nv_bfloat16*)d_in[1];
    const __nv_bfloat16* pw = (const __nv_bfloat16*)d_in[2];
    const int pixels = in_sizes[0] / kC;

    static EncodeTiledFn encode = nullptr;
    static int grid = 0;
    if (!encode) {
        void* fn = nullptr;
        cudaDriverEntryPointQueryResult qr;
        cudaGetDriverEntryPoint("cuTensorMapEncodeTiled", &fn, cudaEnableDefault, &qr);
        encode = (EncodeTiledFn)fn;
        cudaFuncSetAttribute(dwsep_kernel, cudaFuncAttributeMaxDynamicSharedMemorySize, kSmemBytes);
        int sms = 0, clusters = 0;
        cudaDeviceGetAttribute(&sms, cudaDevAttrMultiProcessorCount, 0);
        cudaLaunchConfig_t cfg = {};
        cudaLaunchAttribute attr = {};
        attr.id = cudaLaunchAttributeClusterDimension;
        attr.val.clusterDim.x = 2;
        attr.val.clusterDim.y = attr.val.clusterDim.z = 1;
        cfg.gridDim = dim3(sms & ~1);
        cfg.blockDim = dim3(kThreads);
        cfg.dynamicSmemBytes = kSmemBytes;
        cfg.attrs = &attr;
        cfg.numAttrs = 1;
        if (cudaOccupancyMaxActiveClusters(&clusters, dwsep_kernel, &cfg) != cudaSuccess || clusters < 1) {
            (void)cudaGetLastError();
            clusters = sms / 2;
        }
        grid = 2 * (clusters < sms / 2 ? clusters : sms / 2);
    }

    CUtensorMap tm_w, tm_x0, tm_x, tm_o, tm_pull;
    auto make_map = [&](CUtensorMap* m, const void* base, int rank, const cuuint64_t* dims, const cuuint64_t* strides,
                        const cuuint32_t* box, CUtensorMapL2promotion promo) {
        const cuuint32_t ones[4] = {1, 1, 1, 1};
        encode(m, CU_TENSOR_MAP_DATA_TYPE_BFLOAT16, rank, (void*)base, dims, strides, box, ones,
               CU_TENSOR_MAP_INTERLEAVE_NONE, CU_TENSOR_MAP_SWIZZLE_128B, promo, CU_TENSOR_MAP_FLOAT_OOB_FILL_NONE);
    };
    {
        const cuuint64_t dims[3] = {64, kC, 6}, strides[2] = {kC * 2, 128};
        const cuuint32_t box[3] = {64, 64, 3};
        make_map(&tm_w, pw, 3, dims, strides, box, CU_TENSOR_MAP_L2_PROMOTION_L2_128B);
    }
    {
        const cuuint64_t dims[4] = {64, 8, 6, (cuuint64_t)pixels / 8}, strides[3] = {kC * 2, 128, kC * 2 * 8};
        const cuuint32_t box0[4] = {64, 8, 2, 8}, box[4] = {64, 8, 6, kTilePx / 8};
        make_map(&tm_x0, x, 4, dims, strides, box0, CU_TENSOR_MAP_L2_PROMOTION_L2_128B);
        make_map(&tm_x, x, 4, dims, strides, box, CU_TENSOR_MAP_L2_PROMOTION_L2_128B);
    }
    {
        const cuuint64_t dims[3] = {64, 6, (cuuint64_t)pixels}, strides[2] = {128, kC * 2};
        const cuuint32_t box[3] = {64, 3, kTilePx};
        make_map(&tm_o, d_out, 3, dims, strides, box, CU_TENSOR_MAP_L2_PROMOTION_NONE);
    }
    {
        const cuuint64_t dims[2] = {64, (cuuint64_t)pixels * 6}, strides[1] = {128};
        const cuuint32_t box[2] = {8, 192}, ones[2] = {1, 1};
        encode(&tm_pull, CU_TENSOR_MAP_DATA_TYPE_BFLOAT16, 2, (void*)x, dims, strides, box, ones, CU_TENSOR_MAP_INTERLEAVE_NONE,
               CU_TENSOR_MAP_SWIZZLE_NONE, CU_TENSOR_MAP_L2_PROMOTION_L2_128B, CU_TENSOR_MAP_FLOAT_OOB_FILL_NONE);
    }
    Knobs kn = g_knobs;
    for (int k = 0; k < kLeadPts; k++)
        kn.lead_slope[k] = k < kLeadPts - 1 ? (kn.lead[k + 1] - kn.lead[k]) * 65536 / (kn.lead_pos[k + 1] - kn.lead_pos[k]) : 0;
    dwsep_kernel<<<grid, kThreads, kSmemBytes, cudaStreamPerThread>>>(tm_w, tm_x0, tm_x, tm_o, tm_pull, x, dw, pw,
                                                                      pixels / kTilePx, kn.mid_from, kn.mid_to, kn.mid_n,
                                                                      kn.park_from, kn.static_tiles, kn.stream_from, kn);
}
```
